```python
import torch

def _softmax(x, axis=-1):
    return torch.softmax(x, dim=axis)
def _gelu(x):
    return torch.nn.functional.gelu(x, approximate="tanh")
def _silu(x):
    return torch.nn.functional.silu(x)
def _sigmoid(x):
    return torch.sigmoid(x)
def _layernorm(x, axis=-1, eps=1e-5):
    m = x.mean(dim=axis, keepdim=True)
    v = x.var(dim=axis, keepdim=True, unbiased=False)
    return (x - m) / torch.sqrt(v + eps)
def _scatter_add(tgt, idx, src, axis=0):
    return tgt.clone().index_add_(axis, idx, src)
def _segment_sum(src, seg, n):
    out = torch.zeros((n,) + src.shape[1:], dtype=src.dtype)
    return out.index_add_(0, seg, src)
def _pad(x, pw):
    flat = tuple(v for pair in reversed(pw) for v in pair)
    return torch.nn.functional.pad(x, flat)

kernel_name = 'gated_mix__ssm_conv_s4d__swiglu_ffn__prompt'

def setup_inputs():

    _w = (lambda a: (lambda t: t.to(torch.bfloat16) if t.is_floating_point() else t)(torch.as_tensor(a)))
    def _A_setup():
        Bsz, L, D, N = 1, 2048, 512, 128
        return {
            "u": _w((lambda *s: torch.randn(*s, dtype=torch.bfloat16) * 0.05)(Bsz, L, D)),
            "log_A_real": _w((lambda *s: torch.randn(*s, dtype=torch.bfloat16) * 6.4)(D, N) * 0.5),
            "A_imag": _w((lambda *s: torch.randn(*s, dtype=torch.bfloat16) * 0.05)(D, N) * 3.14),
            "C_real": _w((lambda *s: torch.randn(*s, dtype=torch.bfloat16) * 0.05)(D, N) / N ** 0.5),
            "C_imag": _w((lambda *s: torch.randn(*s, dtype=torch.bfloat16) * 0.05)(D, N) / N ** 0.5),
            "log_dt": _w((lambda *s: torch.randn(*s, dtype=torch.bfloat16) * 0.05)(D) * 0.5 - 4.0),
            "D_skip": _w((lambda *s: torch.randn(*s, dtype=torch.bfloat16) * 0.05)(D)),
        }
    _A_in = _A_setup()

    def _B_setup():
        B, S, D, F = 1, 2048, 512, 1376
        return {
            "x": _w((lambda *s: torch.randn(*s, dtype=torch.bfloat16) * 0.05)(B, S, D)),
            "w_gate": _w((lambda *s: torch.randn(*s, dtype=torch.bfloat16) * 0.05)(D, F)),
            "w_up": _w((lambda *s: torch.randn(*s, dtype=torch.bfloat16) * 0.05)(D, F)),
            "w_down": _w((lambda *s: torch.randn(*s, dtype=torch.bfloat16) * 0.05)(F, D)),
        }
    _B_in = _B_setup()

    return {
        "A_u": _A_in["u"],
        "A_log_A_real": _A_in["log_A_real"],
        "A_A_imag": _A_in["A_imag"],
        "A_C_real": _A_in["C_real"],
        "A_C_imag": _A_in["C_imag"],
        "A_log_dt": _A_in["log_dt"],
        "A_D_skip": _A_in["D_skip"],
        "B_x": _B_in["x"],
        "B_w_gate": _B_in["w_gate"],
        "B_w_up": _B_in["w_up"],
        "B_w_down": _B_in["w_down"],
        "gate_w": _w((lambda *s: torch.randn(*s, dtype=torch.bfloat16) * 0.05)(512) * 16.0),
    }

def reference(A_u, A_log_A_real, A_A_imag, A_C_real, A_C_imag, A_log_dt, A_D_skip, B_x, B_w_gate, B_w_up, B_w_down, gate_w):
    def _A_ref(u, log_A_real, A_imag, C_real, C_imag, log_dt, D_skip):
        L = u.shape[1]
        dt = torch.exp(log_dt)
        A = -torch.exp(log_A_real) + 1j * A_imag
        C = (C_real + 1j * C_imag) * dt[:, None]
        pos = (lambda x, dt: x.to(dt))(torch.arange(L), log_dt.dtype)
        P = torch.exp((A * dt[:, None])[:, :, None] * pos[None, None, :])
        K = 2.0 * torch.einsum("dn,dnl->dl", C, P).real
        L2 = 2 * L
        u_t = (lambda x, *d: x.permute(*d))(u, 0, 2, 1)
        Kf = (lambda x, *a, **k: torch.fft.rfft(x.float(), *a, **k))(K, L2)
        Uf = (lambda x, *a, **k: torch.fft.rfft(x.float(), *a, **k))(u_t, L2)
        y = (lambda x, *a, **k: torch.fft.irfft(x, *a, **k).to(torch.bfloat16))(Uf * Kf[None, :, :], L2)[:, :, :L]
        y = (lambda x, *d: x.permute(*d))(y, 0, 2, 1)
        return y + u * D_skip[None, None, :]

    def _B_ref(x, w_gate, w_up, w_down):
        g = _silu(x @ w_gate)
        u = x @ w_up
        return (g * u) @ w_down

    x = A_u
    g = _sigmoid((x * gate_w).sum(-1, keepdims=True))
    a = _A_ref(x, A_log_A_real, A_A_imag, A_C_real, A_C_imag, A_log_dt, A_D_skip)
    b = _B_ref(x, B_w_gate, B_w_up, B_w_down)
    return g * a + (1 - g) * b
```

```cpp
#include <cuda_runtime.h>
#include <cuda_bf16.h>
#include <cuda_fp16.h>
#include <cuda.h>
#include <stdint.h>

#define HGROUP 1

namespace {

constexpr int kL = 2048, kD = 512, kF = 1376;

constexpr uint32_t SLOT1   = 32768;
constexpr uint32_t OFF_P   = 0;
constexpr uint32_t OFF_XB  = 16384;
constexpr uint32_t OFF_G2  = 32768;
constexpr uint32_t STAGE2  = 24576;
constexpr uint32_t OFF_A   = 163840;
constexpr uint32_t KT_COPY = 4208;
constexpr uint32_t KT_CH   = 2 * KT_COPY;
constexpr uint32_t UT_PAR  = 2112;
constexpr uint32_t UT_CH   = 4288;
constexpr uint32_t OFF_UT  = 181248;
constexpr uint32_t OFF_H7  = OFF_UT + 3 * UT_CH;
constexpr uint32_t OFF_PARK = OFF_UT + 4 * UT_CH;
constexpr uint32_t OFF_BAR = 202304;
constexpr uint32_t OFF_KS  = 202752;
constexpr uint32_t OFF_KT23 = OFF_KS + 11840;
constexpr uint32_t KC_CH   = 2048;
constexpr uint32_t OFF_GATE = 231424;
constexpr uint32_t OFF_TL  = 231680;
constexpr uint32_t SMEM_BYTES = OFF_TL + 512;

constexpr uint32_t B_FULL1 = OFF_BAR, B_EMPTY1 = B_FULL1 + 40, B_G1DONE = B_EMPTY1 + 40;
constexpr uint32_t B_FULL2 = B_G1DONE + 8;
constexpr uint32_t B_EMPTY2 = B_FULL2 + 64;
constexpr uint32_t B_C01 = B_EMPTY2 + 64, B_C2 = B_C01 + 8, B_XD = B_C2 + 8, B_PEMPTY = B_XD + 8, B_TAB23 = B_PEMPTY + 32;
constexpr uint32_t B_XFULL = B_TAB23 + 8, B_YFULL = B_XFULL + 8, B_UFULL = B_YFULL + 8;
constexpr uint32_t B_XTFULL = B_UFULL + 8, B_DONE = B_XTFULL + 8;
constexpr uint32_t OFF_EPOCH = B_DONE + 8;

__host__ __device__ constexpr uint32_t ut_off(int c) { return OFF_UT + (c ^ (c >> 1)) * UT_CH; }
__host__ __device__ constexpr uint32_t w_slot(uint32_t s) { return s < 5 ? OFF_G2 + s * STAGE2 : s == 5 ? OFF_XB : s == 6 ? OFF_A : OFF_KS; }
__host__ __device__ constexpr uint32_t h_slot(uint32_t s) { return s < 5 ? OFF_G2 + s * STAGE2 + 16384 : s == 5 ? OFF_G2 + 5 * STAGE2 : s == 6 ? OFF_A + 16384 : OFF_H7; }

enum { NB_SKEW = 1, NB_H0, NB_H1, NB_C0GO, NB_TAB01, NB_PFULL0, NB_PFULL1, NB_AUX, NB_UT, NB_G, NB_G2GO, NB_INIT };

constexpr int PF_W = 1376;
constexpr int FLAG_STRIDE = 32;
constexpr int FL_H = 0, FL_U = 32, FL_Y = 40, FL_G = 44;

}

__device__ __align__(1024) uint8_t g_h[32 * 88 * 2048];
__device__ __align__(1024) uint8_t g_y[32 * 512 * 128];
__device__ __align__(1024) uint8_t g_u[2 * 512 * 2048];
__device__ __align__(256) uint32_t g_gate[kL];
__device__ uint32_t g_flags[60 * FLAG_STRIDE];
#define TL(id)
#define TLW(id)

namespace {

__device__ __forceinline__ void mma_g1(float (&d)[88], uint32_t alo, uint32_t blo, int scale) {
  asm volatile("{\n.reg .pred p;\n.reg .b64 da, db;\nsetp.ne.b32 p, %90, 0;\nmov.b64 da, {%88, %91};\nmov.b64 db, {%89, %92};\n"
    "wgmma.mma_async.sync.aligned.m64n176k16.f32.bf16.bf16 {%0,%1,%2,%3,%4,%5,%6,%7,%8,%9,%10,%11,%12,%13,%14,%15,%16,%17,%18,%19,%20,%21,%22,%23,%24,%25,%26,%27,%28,%29,%30,%31,%32,%33,%34,%35,%36,%37,%38,%39,%40,%41,%42,%43,%44,%45,%46,%47,%48,%49,%50,%51,%52,%53,%54,%55,%56,%57,%58,%59,%60,%61,%62,%63,%64,%65,%66,%67,%68,%69,%70,%71,%72,%73,%74,%75,%76,%77,%78,%79,%80,%81,%82,%83,%84,%85,%86,%87}, da, db, p, 1, 1, 0, 1;\n}\n"
    : "+f"(d[0]),"+f"(d[1]),"+f"(d[2]),"+f"(d[3]),"+f"(d[4]),"+f"(d[5]),"+f"(d[6]),"+f"(d[7]),"+f"(d[8]),"+f"(d[9]),"+f"(d[10]),"+f"(d[11]),"+f"(d[12]),"+f"(d[13]),"+f"(d[14]),"+f"(d[15]),"+f"(d[16]),"+f"(d[17]),"+f"(d[18]),"+f"(d[19]),"+f"(d[20]),"+f"(d[21]),"+f"(d[22]),"+f"(d[23]),"+f"(d[24]),"+f"(d[25]),"+f"(d[26]),"+f"(d[27]),"+f"(d[28]),"+f"(d[29]),"+f"(d[30]),"+f"(d[31]),"+f"(d[32]),"+f"(d[33]),"+f"(d[34]),"+f"(d[35]),"+f"(d[36]),"+f"(d[37]),"+f"(d[38]),"+f"(d[39]),"+f"(d[40]),"+f"(d[41]),"+f"(d[42]),"+f"(d[43]),"+f"(d[44]),"+f"(d[45]),"+f"(d[46]),"+f"(d[47]),"+f"(d[48]),"+f"(d[49]),"+f"(d[50]),"+f"(d[51]),"+f"(d[52]),"+f"(d[53]),"+f"(d[54]),"+f"(d[55]),"+f"(d[56]),"+f"(d[57]),"+f"(d[58]),"+f"(d[59]),"+f"(d[60]),"+f"(d[61]),"+f"(d[62]),"+f"(d[63]),"+f"(d[64]),"+f"(d[65]),"+f"(d[66]),"+f"(d[67]),"+f"(d[68]),"+f"(d[69]),"+f"(d[70]),"+f"(d[71]),"+f"(d[72]),"+f"(d[73]),"+f"(d[74]),"+f"(d[75]),"+f"(d[76]),"+f"(d[77]),"+f"(d[78]),"+f"(d[79]),"+f"(d[80]),"+f"(d[81]),"+f"(d[82]),"+f"(d[83]),"+f"(d[84]),"+f"(d[85]),"+f"(d[86]),"+f"(d[87])
    : "r"(alo), "r"(blo), "r"(scale), "n"(-2147483616), "n"(1073741888));
}
__device__ __forceinline__ void mma_g2(float (&d)[64], uint32_t alo, uint32_t blo, int scale) {
  asm volatile("{\n.reg .pred p;\n.reg .b64 da, db;\nsetp.ne.b32 p, %66, 0;\nmov.b64 da, {%64, %67};\nmov.b64 db, {%65, %68};\n"
    "wgmma.mma_async.sync.aligned.m64n128k16.f32.bf16.bf16 {%0,%1,%2,%3,%4,%5,%6,%7,%8,%9,%10,%11,%12,%13,%14,%15,%16,%17,%18,%19,%20,%21,%22,%23,%24,%25,%26,%27,%28,%29,%30,%31,%32,%33,%34,%35,%36,%37,%38,%39,%40,%41,%42,%43,%44,%45,%46,%47,%48,%49,%50,%51,%52,%53,%54,%55,%56,%57,%58,%59,%60,%61,%62,%63}, da, db, p, 1, 1, 0, 1;\n}\n"
    : "+f"(d[0]),"+f"(d[1]),"+f"(d[2]),"+f"(d[3]),"+f"(d[4]),"+f"(d[5]),"+f"(d[6]),"+f"(d[7]),"+f"(d[8]),"+f"(d[9]),"+f"(d[10]),"+f"(d[11]),"+f"(d[12]),"+f"(d[13]),"+f"(d[14]),"+f"(d[15]),"+f"(d[16]),"+f"(d[17]),"+f"(d[18]),"+f"(d[19]),"+f"(d[20]),"+f"(d[21]),"+f"(d[22]),"+f"(d[23]),"+f"(d[24]),"+f"(d[25]),"+f"(d[26]),"+f"(d[27]),"+f"(d[28]),"+f"(d[29]),"+f"(d[30]),"+f"(d[31]),"+f"(d[32]),"+f"(d[33]),"+f"(d[34]),"+f"(d[35]),"+f"(d[36]),"+f"(d[37]),"+f"(d[38]),"+f"(d[39]),"+f"(d[40]),"+f"(d[41]),"+f"(d[42]),"+f"(d[43]),"+f"(d[44]),"+f"(d[45]),"+f"(d[46]),"+f"(d[47]),"+f"(d[48]),"+f"(d[49]),"+f"(d[50]),"+f"(d[51]),"+f"(d[52]),"+f"(d[53]),"+f"(d[54]),"+f"(d[55]),"+f"(d[56]),"+f"(d[57]),"+f"(d[58]),"+f"(d[59]),"+f"(d[60]),"+f"(d[61]),"+f"(d[62]),"+f"(d[63])
    : "r"(alo), "r"(blo), "r"(scale), "n"(8), "n"(1073741888));
}
__device__ __forceinline__ void mma_kgen(float (&d)[24], uint32_t alo, uint32_t blo, int scale) {
  asm volatile("{\n.reg .pred p;\n.reg .b64 da, db;\nsetp.ne.b32 p, %26, 0;\nmov.b64 da, {%24, %27};\nmov.b64 db, {%25, %28};\n"
    "wgmma.mma_async.sync.aligned.m64n48k16.f32.f16.f16 {%0,%1,%2,%3,%4,%5,%6,%7,%8,%9,%10,%11,%12,%13,%14,%15,%16,%17,%18,%19,%20,%21,%22,%23}, da, db, p, 1, 1, 1, 1;\n}\n"
    : "+f"(d[0]),"+f"(d[1]),"+f"(d[2]),"+f"(d[3]),"+f"(d[4]),"+f"(d[5]),"+f"(d[6]),"+f"(d[7]),"+f"(d[8]),"+f"(d[9]),"+f"(d[10]),"+f"(d[11]),"+f"(d[12]),"+f"(d[13]),"+f"(d[14]),"+f"(d[15]),"+f"(d[16]),"+f"(d[17]),"+f"(d[18]),"+f"(d[19]),"+f"(d[20]),"+f"(d[21]),"+f"(d[22]),"+f"(d[23])
    : "r"(alo), "r"(blo), "r"(scale), "n"(128), "n"(128));
}
template<int N> __device__ __forceinline__ void mma_conv(float (&d)[64], uint32_t alo, uint32_t blo, int scale);
template<> __device__ __forceinline__ void mma_conv<8>(float (&d)[64], uint32_t alo, uint32_t blo, int scale) {
  asm volatile("{\n.reg .pred p;\n.reg .b64 da, db;\nsetp.ne.b32 p, %6, 0;\nmov.b64 da, {%4, %7};\nmov.b64 db, {%5, %8};\n"
    "wgmma.mma_async.sync.aligned.m64n8k16.f32.bf16.bf16 {%0,%1,%2,%3}, da, db, p, 1, 1, 1, 0;\n}\n"
    : "+f"(d[0]),"+f"(d[1]),"+f"(d[2]),"+f"(d[3])
    : "r"(alo), "r"(blo), "r"(scale), "n"(1), "n"(8));
}
template<> __device__ __forceinline__ void mma_conv<16>(float (&d)[64], uint32_t alo, uint32_t blo, int scale) {
  asm volatile("{\n.reg .pred p;\n.reg .b64 da, db;\nsetp.ne.b32 p, %10, 0;\nmov.b64 da, {%8, %11};\nmov.b64 db, {%9, %12};\n"
    "wgmma.mma_async.sync.aligned.m64n16k16.f32.bf16.bf16 {%0,%1,%2,%3,%4,%5,%6,%7}, da, db, p, 1, 1, 1, 0;\n}\n"
    : "+f"(d[0]),"+f"(d[1]),"+f"(d[2]),"+f"(d[3]),"+f"(d[4]),"+f"(d[5]),"+f"(d[6]),"+f"(d[7])
    : "r"(alo), "r"(blo), "r"(scale), "n"(1), "n"(8));
}
template<> __device__ __forceinline__ void mma_conv<24>(float (&d)[64], uint32_t alo, uint32_t blo, int scale) {
  asm volatile("{\n.reg .pred p;\n.reg .b64 da, db;\nsetp.ne.b32 p, %14, 0;\nmov.b64 da, {%12, %15};\nmov.b64 db, {%13, %16};\n"
    "wgmma.mma_async.sync.aligned.m64n24k16.f32.bf16.bf16 {%0,%1,%2,%3,%4,%5,%6,%7,%8,%9,%10,%11}, da, db, p, 1, 1, 1, 0;\n}\n"
    : "+f"(d[0]),"+f"(d[1]),"+f"(d[2]),"+f"(d[3]),"+f"(d[4]),"+f"(d[5]),"+f"(d[6]),"+f"(d[7]),"+f"(d[8]),"+f"(d[9]),"+f"(d[10]),"+f"(d[11])
    : "r"(alo), "r"(blo), "r"(scale), "n"(1), "n"(8));
}
template<> __device__ __forceinline__ void mma_conv<32>(float (&d)[64], uint32_t alo, uint32_t blo, int scale) {
  asm volatile("{\n.reg .pred p;\n.reg .b64 da, db;\nsetp.ne.b32 p, %18, 0;\nmov.b64 da, {%16, %19};\nmov.b64 db, {%17, %20};\n"
    "wgmma.mma_async.sync.aligned.m64n32k16.f32.bf16.bf16 {%0,%1,%2,%3,%4,%5,%6,%7,%8,%9,%10,%11,%12,%13,%14,%15}, da, db, p, 1, 1, 1, 0;\n}\n"
    : "+f"(d[0]),"+f"(d[1]),"+f"(d[2]),"+f"(d[3]),"+f"(d[4]),"+f"(d[5]),"+f"(d[6]),"+f"(d[7]),"+f"(d[8]),"+f"(d[9]),"+f"(d[10]),"+f"(d[11]),"+f"(d[12]),"+f"(d[13]),"+f"(d[14]),"+f"(d[15])
    : "r"(alo), "r"(blo), "r"(scale), "n"(1), "n"(8));
}
template<> __device__ __forceinline__ void mma_conv<40>(float (&d)[64], uint32_t alo, uint32_t blo, int scale) {
  asm volatile("{\n.reg .pred p;\n.reg .b64 da, db;\nsetp.ne.b32 p, %22, 0;\nmov.b64 da, {%20, %23};\nmov.b64 db, {%21, %24};\n"
    "wgmma.mma_async.sync.aligned.m64n40k16.f32.bf16.bf16 {%0,%1,%2,%3,%4,%5,%6,%7,%8,%9,%10,%11,%12,%13,%14,%15,%16,%17,%18,%19}, da, db, p, 1, 1, 1, 0;\n}\n"
    : "+f"(d[0]),"+f"(d[1]),"+f"(d[2]),"+f"(d[3]),"+f"(d[4]),"+f"(d[5]),"+f"(d[6]),"+f"(d[7]),"+f"(d[8]),"+f"(d[9]),"+f"(d[10]),"+f"(d[11]),"+f"(d[12]),"+f"(d[13]),"+f"(d[14]),"+f"(d[15]),"+f"(d[16]),"+f"(d[17]),"+f"(d[18]),"+f"(d[19])
    : "r"(alo), "r"(blo), "r"(scale), "n"(1), "n"(8));
}
template<> __device__ __forceinline__ void mma_conv<48>(float (&d)[64], uint32_t alo, uint32_t blo, int scale) {
  asm volatile("{\n.reg .pred p;\n.reg .b64 da, db;\nsetp.ne.b32 p, %26, 0;\nmov.b64 da, {%24, %27};\nmov.b64 db, {%25, %28};\n"
    "wgmma.mma_async.sync.aligned.m64n48k16.f32.bf16.bf16 {%0,%1,%2,%3,%4,%5,%6,%7,%8,%9,%10,%11,%12,%13,%14,%15,%16,%17,%18,%19,%20,%21,%22,%23}, da, db, p, 1, 1, 1, 0;\n}\n"
    : "+f"(d[0]),"+f"(d[1]),"+f"(d[2]),"+f"(d[3]),"+f"(d[4]),"+f"(d[5]),"+f"(d[6]),"+f"(d[7]),"+f"(d[8]),"+f"(d[9]),"+f"(d[10]),"+f"(d[11]),"+f"(d[12]),"+f"(d[13]),"+f"(d[14]),"+f"(d[15]),"+f"(d[16]),"+f"(d[17]),"+f"(d[18]),"+f"(d[19]),"+f"(d[20]),"+f"(d[21]),"+f"(d[22]),"+f"(d[23])
    : "r"(alo), "r"(blo), "r"(scale), "n"(1), "n"(8));
}
template<> __device__ __forceinline__ void mma_conv<56>(float (&d)[64], uint32_t alo, uint32_t blo, int scale) {
  asm volatile("{\n.reg .pred p;\n.reg .b64 da, db;\nsetp.ne.b32 p, %30, 0;\nmov.b64 da, {%28, %31};\nmov.b64 db, {%29, %32};\n"
    "wgmma.mma_async.sync.aligned.m64n56k16.f32.bf16.bf16 {%0,%1,%2,%3,%4,%5,%6,%7,%8,%9,%10,%11,%12,%13,%14,%15,%16,%17,%18,%19,%20,%21,%22,%23,%24,%25,%26,%27}, da, db, p, 1, 1, 1, 0;\n}\n"
    : "+f"(d[0]),"+f"(d[1]),"+f"(d[2]),"+f"(d[3]),"+f"(d[4]),"+f"(d[5]),"+f"(d[6]),"+f"(d[7]),"+f"(d[8]),"+f"(d[9]),"+f"(d[10]),"+f"(d[11]),"+f"(d[12]),"+f"(d[13]),"+f"(d[14]),"+f"(d[15]),"+f"(d[16]),"+f"(d[17]),"+f"(d[18]),"+f"(d[19]),"+f"(d[20]),"+f"(d[21]),"+f"(d[22]),"+f"(d[23]),"+f"(d[24]),"+f"(d[25]),"+f"(d[26]),"+f"(d[27])
    : "r"(alo), "r"(blo), "r"(scale), "n"(1), "n"(8));
}
template<> __device__ __forceinline__ void mma_conv<64>(float (&d)[64], uint32_t alo, uint32_t blo, int scale) {
  asm volatile("{\n.reg .pred p;\n.reg .b64 da, db;\nsetp.ne.b32 p, %34, 0;\nmov.b64 da, {%32, %35};\nmov.b64 db, {%33, %36};\n"
    "wgmma.mma_async.sync.aligned.m64n64k16.f32.bf16.bf16 {%0,%1,%2,%3,%4,%5,%6,%7,%8,%9,%10,%11,%12,%13,%14,%15,%16,%17,%18,%19,%20,%21,%22,%23,%24,%25,%26,%27,%28,%29,%30,%31}, da, db, p, 1, 1, 1, 0;\n}\n"
    : "+f"(d[0]),"+f"(d[1]),"+f"(d[2]),"+f"(d[3]),"+f"(d[4]),"+f"(d[5]),"+f"(d[6]),"+f"(d[7]),"+f"(d[8]),"+f"(d[9]),"+f"(d[10]),"+f"(d[11]),"+f"(d[12]),"+f"(d[13]),"+f"(d[14]),"+f"(d[15]),"+f"(d[16]),"+f"(d[17]),"+f"(d[18]),"+f"(d[19]),"+f"(d[20]),"+f"(d[21]),"+f"(d[22]),"+f"(d[23]),"+f"(d[24]),"+f"(d[25]),"+f"(d[26]),"+f"(d[27]),"+f"(d[28]),"+f"(d[29]),"+f"(d[30]),"+f"(d[31])
    : "r"(alo), "r"(blo), "r"(scale), "n"(1), "n"(8));
}
template<> __device__ __forceinline__ void mma_conv<72>(float (&d)[64], uint32_t alo, uint32_t blo, int scale) {
  asm volatile("{\n.reg .pred p;\n.reg .b64 da, db;\nsetp.ne.b32 p, %38, 0;\nmov.b64 da, {%36, %39};\nmov.b64 db, {%37, %40};\n"
    "wgmma.mma_async.sync.aligned.m64n72k16.f32.bf16.bf16 {%0,%1,%2,%3,%4,%5,%6,%7,%8,%9,%10,%11,%12,%13,%14,%15,%16,%17,%18,%19,%20,%21,%22,%23,%24,%25,%26,%27,%28,%29,%30,%31,%32,%33,%34,%35}, da, db, p, 1, 1, 1, 0;\n}\n"
    : "+f"(d[0]),"+f"(d[1]),"+f"(d[2]),"+f"(d[3]),"+f"(d[4]),"+f"(d[5]),"+f"(d[6]),"+f"(d[7]),"+f"(d[8]),"+f"(d[9]),"+f"(d[10]),"+f"(d[11]),"+f"(d[12]),"+f"(d[13]),"+f"(d[14]),"+f"(d[15]),"+f"(d[16]),"+f"(d[17]),"+f"(d[18]),"+f"(d[19]),"+f"(d[20]),"+f"(d[21]),"+f"(d[22]),"+f"(d[23]),"+f"(d[24]),"+f"(d[25]),"+f"(d[26]),"+f"(d[27]),"+f"(d[28]),"+f"(d[29]),"+f"(d[30]),"+f"(d[31]),"+f"(d[32]),"+f"(d[33]),"+f"(d[34]),"+f"(d[35])
    : "r"(alo), "r"(blo), "r"(scale), "n"(1), "n"(8));
}
template<> __device__ __forceinline__ void mma_conv<80>(float (&d)[64], uint32_t alo, uint32_t blo, int scale) {
  asm volatile("{\n.reg .pred p;\n.reg .b64 da, db;\nsetp.ne.b32 p, %42, 0;\nmov.b64 da, {%40, %43};\nmov.b64 db, {%41, %44};\n"
    "wgmma.mma_async.sync.aligned.m64n80k16.f32.bf16.bf16 {%0,%1,%2,%3,%4,%5,%6,%7,%8,%9,%10,%11,%12,%13,%14,%15,%16,%17,%18,%19,%20,%21,%22,%23,%24,%25,%26,%27,%28,%29,%30,%31,%32,%33,%34,%35,%36,%37,%38,%39}, da, db, p, 1, 1, 1, 0;\n}\n"
    : "+f"(d[0]),"+f"(d[1]),"+f"(d[2]),"+f"(d[3]),"+f"(d[4]),"+f"(d[5]),"+f"(d[6]),"+f"(d[7]),"+f"(d[8]),"+f"(d[9]),"+f"(d[10]),"+f"(d[11]),"+f"(d[12]),"+f"(d[13]),"+f"(d[14]),"+f"(d[15]),"+f"(d[16]),"+f"(d[17]),"+f"(d[18]),"+f"(d[19]),"+f"(d[20]),"+f"(d[21]),"+f"(d[22]),"+f"(d[23]),"+f"(d[24]),"+f"(d[25]),"+f"(d[26]),"+f"(d[27]),"+f"(d[28]),"+f"(d[29]),"+f"(d[30]),"+f"(d[31]),"+f"(d[32]),"+f"(d[33]),"+f"(d[34]),"+f"(d[35]),"+f"(d[36]),"+f"(d[37]),"+f"(d[38]),"+f"(d[39])
    : "r"(alo), "r"(blo), "r"(scale), "n"(1), "n"(8));
}
template<> __device__ __forceinline__ void mma_conv<88>(float (&d)[64], uint32_t alo, uint32_t blo, int scale) {
  asm volatile("{\n.reg .pred p;\n.reg .b64 da, db;\nsetp.ne.b32 p, %46, 0;\nmov.b64 da, {%44, %47};\nmov.b64 db, {%45, %48};\n"
    "wgmma.mma_async.sync.aligned.m64n88k16.f32.bf16.bf16 {%0,%1,%2,%3,%4,%5,%6,%7,%8,%9,%10,%11,%12,%13,%14,%15,%16,%17,%18,%19,%20,%21,%22,%23,%24,%25,%26,%27,%28,%29,%30,%31,%32,%33,%34,%35,%36,%37,%38,%39,%40,%41,%42,%43}, da, db, p, 1, 1, 1, 0;\n}\n"
    : "+f"(d[0]),"+f"(d[1]),"+f"(d[2]),"+f"(d[3]),"+f"(d[4]),"+f"(d[5]),"+f"(d[6]),"+f"(d[7]),"+f"(d[8]),"+f"(d[9]),"+f"(d[10]),"+f"(d[11]),"+f"(d[12]),"+f"(d[13]),"+f"(d[14]),"+f"(d[15]),"+f"(d[16]),"+f"(d[17]),"+f"(d[18]),"+f"(d[19]),"+f"(d[20]),"+f"(d[21]),"+f"(d[22]),"+f"(d[23]),"+f"(d[24]),"+f"(d[25]),"+f"(d[26]),"+f"(d[27]),"+f"(d[28]),"+f"(d[29]),"+f"(d[30]),"+f"(d[31]),"+f"(d[32]),"+f"(d[33]),"+f"(d[34]),"+f"(d[35]),"+f"(d[36]),"+f"(d[37]),"+f"(d[38]),"+f"(d[39]),"+f"(d[40]),"+f"(d[41]),"+f"(d[42]),"+f"(d[43])
    : "r"(alo), "r"(blo), "r"(scale), "n"(1), "n"(8));
}
template<> __device__ __forceinline__ void mma_conv<96>(float (&d)[64], uint32_t alo, uint32_t blo, int scale) {
  asm volatile("{\n.reg .pred p;\n.reg .b64 da, db;\nsetp.ne.b32 p, %50, 0;\nmov.b64 da, {%48, %51};\nmov.b64 db, {%49, %52};\n"
    "wgmma.mma_async.sync.aligned.m64n96k16.f32.bf16.bf16 {%0,%1,%2,%3,%4,%5,%6,%7,%8,%9,%10,%11,%12,%13,%14,%15,%16,%17,%18,%19,%20,%21,%22,%23,%24,%25,%26,%27,%28,%29,%30,%31,%32,%33,%34,%35,%36,%37,%38,%39,%40,%41,%42,%43,%44,%45,%46,%47}, da, db, p, 1, 1, 1, 0;\n}\n"
    : "+f"(d[0]),"+f"(d[1]),"+f"(d[2]),"+f"(d[3]),"+f"(d[4]),"+f"(d[5]),"+f"(d[6]),"+f"(d[7]),"+f"(d[8]),"+f"(d[9]),"+f"(d[10]),"+f"(d[11]),"+f"(d[12]),"+f"(d[13]),"+f"(d[14]),"+f"(d[15]),"+f"(d[16]),"+f"(d[17]),"+f"(d[18]),"+f"(d[19]),"+f"(d[20]),"+f"(d[21]),"+f"(d[22]),"+f"(d[23]),"+f"(d[24]),"+f"(d[25]),"+f"(d[26]),"+f"(d[27]),"+f"(d[28]),"+f"(d[29]),"+f"(d[30]),"+f"(d[31]),"+f"(d[32]),"+f"(d[33]),"+f"(d[34]),"+f"(d[35]),"+f"(d[36]),"+f"(d[37]),"+f"(d[38]),"+f"(d[39]),"+f"(d[40]),"+f"(d[41]),"+f"(d[42]),"+f"(d[43]),"+f"(d[44]),"+f"(d[45]),"+f"(d[46]),"+f"(d[47])
    : "r"(alo), "r"(blo), "r"(scale), "n"(1), "n"(8));
}
template<> __device__ __forceinline__ void mma_conv<104>(float (&d)[64], uint32_t alo, uint32_t blo, int scale) {
  asm volatile("{\n.reg .pred p;\n.reg .b64 da, db;\nsetp.ne.b32 p, %54, 0;\nmov.b64 da, {%52, %55};\nmov.b64 db, {%53, %56};\n"
    "wgmma.mma_async.sync.aligned.m64n104k16.f32.bf16.bf16 {%0,%1,%2,%3,%4,%5,%6,%7,%8,%9,%10,%11,%12,%13,%14,%15,%16,%17,%18,%19,%20,%21,%22,%23,%24,%25,%26,%27,%28,%29,%30,%31,%32,%33,%34,%35,%36,%37,%38,%39,%40,%41,%42,%43,%44,%45,%46,%47,%48,%49,%50,%51}, da, db, p, 1, 1, 1, 0;\n}\n"
    : "+f"(d[0]),"+f"(d[1]),"+f"(d[2]),"+f"(d[3]),"+f"(d[4]),"+f"(d[5]),"+f"(d[6]),"+f"(d[7]),"+f"(d[8]),"+f"(d[9]),"+f"(d[10]),"+f"(d[11]),"+f"(d[12]),"+f"(d[13]),"+f"(d[14]),"+f"(d[15]),"+f"(d[16]),"+f"(d[17]),"+f"(d[18]),"+f"(d[19]),"+f"(d[20]),"+f"(d[21]),"+f"(d[22]),"+f"(d[23]),"+f"(d[24]),"+f"(d[25]),"+f"(d[26]),"+f"(d[27]),"+f"(d[28]),"+f"(d[29]),"+f"(d[30]),"+f"(d[31]),"+f"(d[32]),"+f"(d[33]),"+f"(d[34]),"+f"(d[35]),"+f"(d[36]),"+f"(d[37]),"+f"(d[38]),"+f"(d[39]),"+f"(d[40]),"+f"(d[41]),"+f"(d[42]),"+f"(d[43]),"+f"(d[44]),"+f"(d[45]),"+f"(d[46]),"+f"(d[47]),"+f"(d[48]),"+f"(d[49]),"+f"(d[50]),"+f"(d[51])
    : "r"(alo), "r"(blo), "r"(scale), "n"(1), "n"(8));
}
template<> __device__ __forceinline__ void mma_conv<112>(float (&d)[64], uint32_t alo, uint32_t blo, int scale) {
  asm volatile("{\n.reg .pred p;\n.reg .b64 da, db;\nsetp.ne.b32 p, %58, 0;\nmov.b64 da, {%56, %59};\nmov.b64 db, {%57, %60};\n"
    "wgmma.mma_async.sync.aligned.m64n112k16.f32.bf16.bf16 {%0,%1,%2,%3,%4,%5,%6,%7,%8,%9,%10,%11,%12,%13,%14,%15,%16,%17,%18,%19,%20,%21,%22,%23,%24,%25,%26,%27,%28,%29,%30,%31,%32,%33,%34,%35,%36,%37,%38,%39,%40,%41,%42,%43,%44,%45,%46,%47,%48,%49,%50,%51,%52,%53,%54,%55}, da, db, p, 1, 1, 1, 0;\n}\n"
    : "+f"(d[0]),"+f"(d[1]),"+f"(d[2]),"+f"(d[3]),"+f"(d[4]),"+f"(d[5]),"+f"(d[6]),"+f"(d[7]),"+f"(d[8]),"+f"(d[9]),"+f"(d[10]),"+f"(d[11]),"+f"(d[12]),"+f"(d[13]),"+f"(d[14]),"+f"(d[15]),"+f"(d[16]),"+f"(d[17]),"+f"(d[18]),"+f"(d[19]),"+f"(d[20]),"+f"(d[21]),"+f"(d[22]),"+f"(d[23]),"+f"(d[24]),"+f"(d[25]),"+f"(d[26]),"+f"(d[27]),"+f"(d[28]),"+f"(d[29]),"+f"(d[30]),"+f"(d[31]),"+f"(d[32]),"+f"(d[33]),"+f"(d[34]),"+f"(d[35]),"+f"(d[36]),"+f"(d[37]),"+f"(d[38]),"+f"(d[39]),"+f"(d[40]),"+f"(d[41]),"+f"(d[42]),"+f"(d[43]),"+f"(d[44]),"+f"(d[45]),"+f"(d[46]),"+f"(d[47]),"+f"(d[48]),"+f"(d[49]),"+f"(d[50]),"+f"(d[51]),"+f"(d[52]),"+f"(d[53]),"+f"(d[54]),"+f"(d[55])
    : "r"(alo), "r"(blo), "r"(scale), "n"(1), "n"(8));
}
template<> __device__ __forceinline__ void mma_conv<120>(float (&d)[64], uint32_t alo, uint32_t blo, int scale) {
  asm volatile("{\n.reg .pred p;\n.reg .b64 da, db;\nsetp.ne.b32 p, %62, 0;\nmov.b64 da, {%60, %63};\nmov.b64 db, {%61, %64};\n"
    "wgmma.mma_async.sync.aligned.m64n120k16.f32.bf16.bf16 {%0,%1,%2,%3,%4,%5,%6,%7,%8,%9,%10,%11,%12,%13,%14,%15,%16,%17,%18,%19,%20,%21,%22,%23,%24,%25,%26,%27,%28,%29,%30,%31,%32,%33,%34,%35,%36,%37,%38,%39,%40,%41,%42,%43,%44,%45,%46,%47,%48,%49,%50,%51,%52,%53,%54,%55,%56,%57,%58,%59}, da, db, p, 1, 1, 1, 0;\n}\n"
    : "+f"(d[0]),"+f"(d[1]),"+f"(d[2]),"+f"(d[3]),"+f"(d[4]),"+f"(d[5]),"+f"(d[6]),"+f"(d[7]),"+f"(d[8]),"+f"(d[9]),"+f"(d[10]),"+f"(d[11]),"+f"(d[12]),"+f"(d[13]),"+f"(d[14]),"+f"(d[15]),"+f"(d[16]),"+f"(d[17]),"+f"(d[18]),"+f"(d[19]),"+f"(d[20]),"+f"(d[21]),"+f"(d[22]),"+f"(d[23]),"+f"(d[24]),"+f"(d[25]),"+f"(d[26]),"+f"(d[27]),"+f"(d[28]),"+f"(d[29]),"+f"(d[30]),"+f"(d[31]),"+f"(d[32]),"+f"(d[33]),"+f"(d[34]),"+f"(d[35]),"+f"(d[36]),"+f"(d[37]),"+f"(d[38]),"+f"(d[39]),"+f"(d[40]),"+f"(d[41]),"+f"(d[42]),"+f"(d[43]),"+f"(d[44]),"+f"(d[45]),"+f"(d[46]),"+f"(d[47]),"+f"(d[48]),"+f"(d[49]),"+f"(d[50]),"+f"(d[51]),"+f"(d[52]),"+f"(d[53]),"+f"(d[54]),"+f"(d[55]),"+f"(d[56]),"+f"(d[57]),"+f"(d[58]),"+f"(d[59])
    : "r"(alo), "r"(blo), "r"(scale), "n"(1), "n"(8));
}
template<> __device__ __forceinline__ void mma_conv<128>(float (&d)[64], uint32_t alo, uint32_t blo, int scale) {
  asm volatile("{\n.reg .pred p;\n.reg .b64 da, db;\nsetp.ne.b32 p, %66, 0;\nmov.b64 da, {%64, %67};\nmov.b64 db, {%65, %68};\n"
    "wgmma.mma_async.sync.aligned.m64n128k16.f32.bf16.bf16 {%0,%1,%2,%3,%4,%5,%6,%7,%8,%9,%10,%11,%12,%13,%14,%15,%16,%17,%18,%19,%20,%21,%22,%23,%24,%25,%26,%27,%28,%29,%30,%31,%32,%33,%34,%35,%36,%37,%38,%39,%40,%41,%42,%43,%44,%45,%46,%47,%48,%49,%50,%51,%52,%53,%54,%55,%56,%57,%58,%59,%60,%61,%62,%63}, da, db, p, 1, 1, 1, 0;\n}\n"
    : "+f"(d[0]),"+f"(d[1]),"+f"(d[2]),"+f"(d[3]),"+f"(d[4]),"+f"(d[5]),"+f"(d[6]),"+f"(d[7]),"+f"(d[8]),"+f"(d[9]),"+f"(d[10]),"+f"(d[11]),"+f"(d[12]),"+f"(d[13]),"+f"(d[14]),"+f"(d[15]),"+f"(d[16]),"+f"(d[17]),"+f"(d[18]),"+f"(d[19]),"+f"(d[20]),"+f"(d[21]),"+f"(d[22]),"+f"(d[23]),"+f"(d[24]),"+f"(d[25]),"+f"(d[26]),"+f"(d[27]),"+f"(d[28]),"+f"(d[29]),"+f"(d[30]),"+f"(d[31]),"+f"(d[32]),"+f"(d[33]),"+f"(d[34]),"+f"(d[35]),"+f"(d[36]),"+f"(d[37]),"+f"(d[38]),"+f"(d[39]),"+f"(d[40]),"+f"(d[41]),"+f"(d[42]),"+f"(d[43]),"+f"(d[44]),"+f"(d[45]),"+f"(d[46]),"+f"(d[47]),"+f"(d[48]),"+f"(d[49]),"+f"(d[50]),"+f"(d[51]),"+f"(d[52]),"+f"(d[53]),"+f"(d[54]),"+f"(d[55]),"+f"(d[56]),"+f"(d[57]),"+f"(d[58]),"+f"(d[59]),"+f"(d[60]),"+f"(d[61]),"+f"(d[62]),"+f"(d[63])
    : "r"(alo), "r"(blo), "r"(scale), "n"(1), "n"(8));
}

__device__ __forceinline__ void wg_fence() { asm volatile("wgmma.fence.sync.aligned;" ::: "memory"); }
__device__ __forceinline__ void wg_commit() { asm volatile("wgmma.commit_group.sync.aligned;" ::: "memory"); }
template <int N> __device__ __forceinline__ void wg_wait() { asm volatile("wgmma.wait_group.sync.aligned %0;" ::"n"(N) : "memory"); }
template <int N> __device__ __forceinline__ void pin(float (&d)[N]) {
#pragma unroll
  for (int i = 0; i < N; i++) asm volatile("" : "+f"(d[i])::"memory");
}

__device__ __forceinline__ void mbar_init(uint32_t b, int c) { asm volatile("mbarrier.init.shared::cta.b64 [%0], %1;" ::"r"(b), "r"(c) : "memory"); }
__device__ __forceinline__ void mbar_arrive(uint32_t b) { asm volatile("mbarrier.arrive.shared::cta.b64 _, [%0];" ::"r"(b) : "memory"); }
__device__ __forceinline__ void mbar_expect(uint32_t b, uint32_t bytes) { asm volatile("mbarrier.arrive.expect_tx.shared::cta.b64 _, [%0], %1;" ::"r"(b), "r"(bytes) : "memory"); }
__device__ __forceinline__ void mbar_wait(uint32_t b, uint32_t parity) {
  asm volatile(
      "{\n.reg .pred p;\n.reg .u32 n;\nmov.u32 n, 0;\n"
      "W:\nmbarrier.try_wait.parity.shared::cta.b64 p, [%0], %1;\n@p bra DONE;\n"
      "add.u32 n, n, 1;\nsetp.lt.u32 p, n, 2000000;\n@p bra W;\ntrap;\nDONE:\n}\n" ::"r"(b), "r"(parity) : "memory");
}
__device__ __forceinline__ bool mbar_test(uint32_t b, uint32_t parity) {
  uint32_t ok;
  asm volatile("{\n.reg .pred p;\nmbarrier.test_wait.parity.shared::cta.b64 p, [%1], %2;\nselp.b32 %0, 1, 0, p;\n}\n" : "=r"(ok) : "r"(b), "r"(parity) : "memory");
  return ok;
}
__device__ __forceinline__ void nb_sync(int id, int n) { asm volatile("bar.sync %0, %1;" ::"r"(id), "r"(n) : "memory"); }
__device__ __forceinline__ void nb_arrive(int id, int n) { asm volatile("bar.arrive %0, %1;" ::"r"(id), "r"(n) : "memory"); }
__device__ __forceinline__ void fence_async_smem() { asm volatile("fence.proxy.async.shared::cta;" ::: "memory"); }
__device__ __forceinline__ void fence_async_all() { asm volatile("fence.proxy.async;" ::: "memory"); }

__device__ __forceinline__ void flag_signal(int f, uint32_t inc) {
  fence_async_all();
  asm volatile("red.relaxed.gpu.global.add.u32 [%0], %1;" ::"l"(g_flags + f * FLAG_STRIDE), "r"(inc) : "memory");
}
__device__ __forceinline__ uint32_t flag_peek(const uint32_t* f) {
  uint32_t v;
  asm volatile("ld.relaxed.gpu.global.u32 %0, [%1];" : "=r"(v) : "l"(f) : "memory");
  return v;
}
__device__ __forceinline__ void flag_wait(int idx, uint32_t target) {
  const uint32_t* f = g_flags + idx * FLAG_STRIDE;
#pragma unroll 1
  for (int i = 0; (int32_t)(flag_peek(f) - target) < 0; i++)
    if (i == 20000000) __trap();
  asm volatile("fence.acquire.gpu;" ::: "memory");
  asm volatile("fence.proxy.async.global;" ::: "memory");
}

__device__ __forceinline__ void tma2d(uint32_t dst, const CUtensorMap* m, uint32_t bar, int c0, int c1) {
  asm volatile("cp.async.bulk.tensor.2d.shared::cluster.global.mbarrier::complete_tx::bytes [%0], [%1, {%3, %4}], [%2];"
               ::"r"(dst), "l"(m), "r"(bar), "r"(c0), "r"(c1) : "memory");
}
__device__ __forceinline__ void tma3d(uint32_t dst, const CUtensorMap* m, uint32_t bar, int c0, int c1, int c2) {
  asm volatile("cp.async.bulk.tensor.3d.shared::cluster.global.mbarrier::complete_tx::bytes [%0], [%1, {%3, %4, %5}], [%2];"
               ::"r"(dst), "l"(m), "r"(bar), "r"(c0), "r"(c1), "r"(c2) : "memory");
}
__device__ __forceinline__ void tma4d(uint32_t dst, const CUtensorMap* m, uint32_t bar, int c0, int c1, int c2, int c3) {
  asm volatile("cp.async.bulk.tensor.4d.shared::cluster.global.mbarrier::complete_tx::bytes [%0], [%1, {%3, %4, %5, %6}], [%2];"
               ::"r"(dst), "l"(m), "r"(bar), "r"(c0), "r"(c1), "r"(c2), "r"(c3) : "memory");
}
__device__ __forceinline__ void tma3d_store(const CUtensorMap* m, uint32_t src, int c0, int c1, int c2) {
  asm volatile("cp.async.bulk.tensor.3d.global.shared::cta.bulk_group [%0, {%2, %3, %4}], [%1];"
               ::"l"(m), "r"(src), "r"(c0), "r"(c1), "r"(c2) : "memory");
}
__device__ __forceinline__ void bulk_load(uint32_t dst, const void* src, uint32_t bytes, uint32_t bar) {
  asm volatile("cp.async.bulk.shared::cluster.global.mbarrier::complete_tx::bytes [%0], [%1], %2, [%3];"
               ::"r"(dst), "l"(src), "r"(bytes), "r"(bar) : "memory");
}
__device__ __forceinline__ bool elect() {
  uint32_t p;
  asm volatile("{\n.reg .pred p;\nelect.sync _|p, 0xffffffff;\nselp.b32 %0, 1, 0, p;\n}\n" : "=r"(p));
  return p;
}

__device__ __forceinline__ uint32_t pack_bf16(float lo, float hi) { uint32_t r; asm("cvt.rn.bf16x2.f32 %0, %1, %2;" : "=r"(r) : "f"(hi), "f"(lo)); return r; }
__device__ __forceinline__ uint32_t pack_f16(float lo, float hi) { uint32_t r; asm("cvt.rn.f16x2.f32 %0, %1, %2;" : "=r"(r) : "f"(hi), "f"(lo)); return r; }
__device__ __forceinline__ uint32_t bmul2(uint32_t a, uint32_t b) { uint32_t r; asm("mul.rn.bf16x2 %0, %1, %2;" : "=r"(r) : "r"(a), "r"(b)); return r; }
__device__ __forceinline__ uint32_t badd2(uint32_t a, uint32_t b) { uint32_t r; asm("add.rn.bf16x2 %0, %1, %2;" : "=r"(r) : "r"(a), "r"(b)); return r; }
__device__ __forceinline__ uint32_t bfma2(uint32_t a, uint32_t b, uint32_t c) { uint32_t r; asm("fma.rn.bf16x2 %0, %1, %2, %3;" : "=r"(r) : "r"(a), "r"(b), "r"(c)); return r; }
__device__ __forceinline__ float bf_lo(uint32_t w) { return __uint_as_float(w << 16); }
__device__ __forceinline__ float bf_hi(uint32_t w) { return __uint_as_float(w & 0xffff0000u); }
__device__ __forceinline__ float bf_round(float v) { return __bfloat162float(__float2bfloat16_rn(v)); }

__device__ __forceinline__ void sts128(uint32_t a, uint32_t x, uint32_t y, uint32_t z, uint32_t w) { asm volatile("st.shared.v4.u32 [%0], {%1, %2, %3, %4};" ::"r"(a), "r"(x), "r"(y), "r"(z), "r"(w) : "memory"); }
__device__ __forceinline__ void sts32(uint32_t a, uint32_t x) { asm volatile("st.shared.u32 [%0], %1;" ::"r"(a), "r"(x) : "memory"); }
__device__ __forceinline__ void sts16(uint32_t a, uint32_t x) { asm volatile("st.shared.u16 [%0], %1;" ::"r"(a), "h"((uint16_t)x) : "memory"); }
__device__ __forceinline__ void stsf(uint32_t a, float x) { asm volatile("st.shared.f32 [%0], %1;" ::"r"(a), "f"(x) : "memory"); }
__device__ __forceinline__ uint32_t lds32(uint32_t a) { uint32_t v; asm volatile("ld.shared.u32 %0, [%1];" : "=r"(v) : "r"(a) : "memory"); return v; }
__device__ __forceinline__ float ldsf(uint32_t a) { float v; asm volatile("ld.shared.f32 %0, [%1];" : "=f"(v) : "r"(a) : "memory"); return v; }
__device__ __forceinline__ float2 ldsf2(uint32_t a) { float2 v; asm volatile("ld.shared.v2.f32 {%0, %1}, [%2];" : "=f"(v.x), "=f"(v.y) : "r"(a) : "memory"); return v; }
__device__ __forceinline__ float4 ldsf4(uint32_t a) { float4 v; asm volatile("ld.shared.v4.f32 {%0, %1, %2, %3}, [%4];" : "=f"(v.x), "=f"(v.y), "=f"(v.z), "=f"(v.w) : "r"(a) : "memory"); return v; }
__device__ __forceinline__ void stsm4(uint32_t a, uint32_t r0, uint32_t r1, uint32_t r2, uint32_t r3) { asm volatile("stmatrix.sync.aligned.m8n8.x4.shared.b16 [%0], {%1, %2, %3, %4};" ::"r"(a), "r"(r0), "r"(r1), "r"(r2), "r"(r3) : "memory"); }
__device__ __forceinline__ void stsm4t(uint32_t a, uint32_t r0, uint32_t r1, uint32_t r2, uint32_t r3) { asm volatile("stmatrix.sync.aligned.m8n8.x4.trans.shared.b16 [%0], {%1, %2, %3, %4};" ::"r"(a), "r"(r0), "r"(r1), "r"(r2), "r"(r3) : "memory"); }
__device__ __forceinline__ void ldsm4(uint32_t a, uint32_t* r) { asm volatile("ldmatrix.sync.aligned.m8n8.x4.shared.b16 {%0, %1, %2, %3}, [%4];" : "=r"(r[0]), "=r"(r[1]), "=r"(r[2]), "=r"(r[3]) : "r"(a) : "memory"); }
__device__ __forceinline__ void ldsm4t(uint32_t a, uint32_t* r) { asm volatile("ldmatrix.sync.aligned.m8n8.x4.trans.shared.b16 {%0, %1, %2, %3}, [%4];" : "=r"(r[0]), "=r"(r[1]), "=r"(r[2]), "=r"(r[3]) : "r"(a) : "memory"); }

struct cf { float r, i; };
__device__ __forceinline__ cf cmul(cf a, cf b) { return {a.r * b.r - a.i * b.i, a.r * b.i + a.i * b.r}; }
__device__ __forceinline__ cf csq(cf a) { return {a.r * a.r - a.i * a.i, (a.r + a.r) * a.i}; }
__device__ __forceinline__ cf cpow_seed(float a2, float beta, float p) {
  float e;
  asm("ex2.approx.ftz.f32 %0, %1;" : "=f"(e) : "f"(a2 * p));
  const float th = beta * p;
  return {e * __cosf(th), e * __sinf(th)};
}
__device__ __forceinline__ void hcmul(uint32_t r, uint32_t i, uint32_t wr, uint32_t wi, uint32_t& ro, uint32_t& io) {
  const __half2 hr = *reinterpret_cast<__half2*>(&r), hi = *reinterpret_cast<__half2*>(&i);
  const __half2 hwr = *reinterpret_cast<__half2*>(&wr), hwi = *reinterpret_cast<__half2*>(&wi);
  __half2 a = __hfma2(hr, hwr, __hneg2(__hmul2(hi, hwi)));
  __half2 b = __hfma2(hr, hwi, __hmul2(hi, hwr));
  ro = *reinterpret_cast<uint32_t*>(&a);
  io = *reinterpret_cast<uint32_t*>(&b);
}

template <int J> struct ConvSeq {
  static __device__ __forceinline__ void run(float (&d)[64], uint32_t a, uint32_t b) {
    mma_conv<128 - 8 * J>(d, a + 16 * J, b + 8 * J, J != 0);
    mma_conv<128 - 8 * J>(d, a + KT_COPY / 16 + 16 * J, b + UT_PAR / 16 + 8 * J, 1);
    ConvSeq<J + 1>::run(d, a, b);
  }
};
template <> struct ConvSeq<16> { static __device__ __forceinline__ void run(float (&)[64], uint32_t, uint32_t) {} };

struct Params {
  const __nv_bfloat16 *x, *log_a, *a_im, *c_re, *c_im, *log_dt, *d_skip, *w_gate, *w_up, *w_down, *gate_w;
};

}

__global__ void __launch_bounds__(512, 1)
gated_mix_kernel(const __grid_constant__ CUtensorMap tm_x, const __grid_constant__ CUtensorMap tm_wg,
                 const __grid_constant__ CUtensorMap tm_wu, const __grid_constant__ CUtensorMap tm_wd,
                 const __grid_constant__ CUtensorMap tm_out,
                 const __grid_constant__ CUtensorMap tm_u, const __grid_constant__ CUtensorMap tm_xp, const Params p) {
  extern __shared__ uint8_t smem_raw[];
  constexpr uint32_t sb = 1024, sd = sb;
  const int warp = __shfl_sync(0xffffffffu, threadIdx.x >> 5, 0);
  const int lane = threadIdx.x & 31;
  const int wg = warp >> 2, w4 = warp & 3;
  const int cta = blockIdx.x;
  const int mb = (cta & 3) + 4 * ((cta >> 3) & 3);
  const int nb = (cta >> 5) + (cta & 4);
  const int tb = 8 * (cta >> 5) + 2 * (cta & 3) + ((cta >> 4) & 1);
  const int cq = (cta >> 2) & 3;
  TL(wg);

  auto g1_load = [&](int ks, uint32_t slot) {
    const uint32_t bar = sb + B_FULL1 + 8 * slot, dst = sb + slot * SLOT1;
    mbar_expect(bar, SLOT1);
    tma2d(dst, &tm_x, bar, 32 * ks, 128 * mb);
#pragma unroll
    for (int m = 0; m < 2; m++) {
      const CUtensorMap* tw = m ? &tm_wu : &tm_wg;
      const uint32_t dw = dst + 8192 + m * 12288;
      tma2d(dw, tw, bar, 64 * nb, 32 * ks);
      tma2d(dw + 4096, tw, bar, 512 + 64 * nb, 32 * ks);
      tma2d(dw + 8192, tw, bar, 1024 + 48 * nb, 32 * ks);
    }
  };

  uint32_t raw[16];
  if (warp == 12) {
    if (elect()) {
#pragma unroll
      for (int i = 0; i < 5; i++) mbar_init(sb + B_FULL1 + 8 * i, 1);
      fence_async_smem();
    }
    __syncwarp();
    nb_arrive(0, 512);
    if (elect()) g1_load(0, 0);
    __syncwarp();
    TL(48);
    nb_sync(NB_INIT, 192);
  } else {
    if (warp >= 13) {
      if (elect()) asm volatile("prefetch.tensormap [%0];" ::"l"(&tm_x + (warp - 13)) : "memory");
    } else if (warp >= 8) {
      const int mu = threadIdx.x & 63;
#pragma unroll
      for (int P = 0; P < 2; P++) {
        const int o = (4 * cta + 2 * P + (w4 >> 1)) * 64;
        raw[6 * P + 0] = __ldg((const uint32_t*)p.log_a + o + mu);
        raw[6 * P + 1] = __ldg((const uint32_t*)p.a_im + o + mu);
        raw[6 * P + 2] = __ldg((const uint32_t*)p.c_re + o + mu);
        raw[6 * P + 3] = __ldg((const uint32_t*)p.c_im + o + mu);
        raw[6 * P + 4] = __ldg((const uint32_t*)p.c_re + o + (mu ^ 32));
        raw[6 * P + 5] = __ldg((const uint32_t*)p.c_im + o + (mu ^ 32));
      }
      raw[12] = __ldg((const uint16_t*)p.log_dt + 4 * cta + (w4 >> 1));
      raw[13] = __ldg((const uint16_t*)p.log_dt + 4 * cta + 2 + (w4 >> 1));
      raw[14] = __ldg((const uint16_t*)p.d_skip + 4 * cta + (w4 >> 1));
      raw[15] = __ldg((const uint16_t*)p.d_skip + 4 * cta + 2 + (w4 >> 1));
    } else if (warp >= 3) {
      if (elect()) {
        const int cnt = warp == 3 ? 8 : warp == 4 ? 2 : warp == 7 ? 1 : 4;
        const int num = warp == 3 ? 6 : warp == 7 ? 5 : 8;
        const uint32_t b0 = sb + (warp == 3 ? B_EMPTY1 : warp == 7 ? B_XFULL : B_FULL2 + 64 * (warp - 4));
#pragma unroll
        for (int i = 0; i < 8; i++)
          if (i < num) mbar_init(b0 + 8 * i, (warp == 7 && i == 4) ? 15 : cnt);
        if ((uint32_t)__cvta_generic_to_shared(smem_raw) != sb) __trap();
        fence_async_smem();
      }
      __syncwarp();
      nb_arrive(NB_INIT, 192);
    } else if (warp == 2) {
      if (lane < 16) asm volatile("prefetch.global.L2 [%0];" ::"l"(p.x + (size_t)(16 * cta + lane) * kD) : "memory");
    } else {
      if (elect()) asm volatile("cp.async.bulk.prefetch.L2.global [%0], %1;" ::"l"((const uint8_t*)(warp ? p.w_up : p.w_gate) + cta * PF_W), "n"(PF_W) : "memory");
    }
    nb_sync(0, 512);
  }
  if (wg == 0) TL(47);

  if (wg == 3) {
    asm volatile("setmaxnreg.dec.sync.aligned.u32 24;");
    if (w4 == 0) {
      uint32_t slot = 1, ph = 1;
#pragma unroll 1
      for (int ks = 1; ks < 16; ks++) {
        mbar_wait(sb + B_EMPTY1 + 8 * slot, ph);
        if (elect()) g1_load(ks, slot);
        __syncwarp();
        if (ks == 4) TL(49);
        if (++slot == 5) { slot = 0; ph ^= 1; }
      }
#pragma unroll 1
      for (int st = 0; st < 22; st++) {
        slot = st & 7;
        if (st < 5) {
          if (st != 3) mbar_wait(sb + B_EMPTY1 + 8 * (st < 3 ? st + 1 : 4), 0);
        } else if (st < 8) {
          mbar_wait(sb + (st == 5 ? B_G1DONE : B_C01 + 8 * (st - 6)), 0);
        } else {
          mbar_wait(sb + B_EMPTY2 + 8 * slot, (st >> 4) & 1);
        }
        if (elect()) {
          const uint32_t bar = sb + B_FULL2 + 8 * slot;
          mbar_expect(bar, 16384);
          tma3d(sb + w_slot(slot), &tm_wd, bar, 0, 64 * st, 2 * cq);
        }
        __syncwarp();
      }
    } else if (w4 == 1) {
      uint32_t target;
      asm volatile("ld.relaxed.gpu.global.u32 %0, [%1];" : "=r"(target) : "l"(g_flags + (FL_U + nb) * FLAG_STRIDE) : "memory");
      target = (target & ~31u) + 32;
      if (elect()) {
        sts32(sb + OFF_EPOCH, target);
#pragma unroll
        for (int i = 3; i >= 0; i--) asm volatile("prefetch.tensormap [%0];" ::"l"(&tm_wd + i) : "memory");
        mbar_expect(sb + B_XTFULL, 16384);
        tma4d(sb + OFF_UT, &tm_xp, sb + B_XTFULL, 64 * nb, 0, 0, 2 * mb);
      }
      __syncwarp();
      nb_sync(NB_UT, 160);
      if (elect()) {
        tma3d_store(&tm_u, sb + OFF_UT, 32 * (30 - 2 * mb), 64 * nb, 0);
        asm volatile("cp.async.bulk.commit_group;" ::: "memory");
        asm volatile("cp.async.bulk.prefetch.L2.global [%0], %1;" ::"l"((const uint8_t*)p.w_down + (size_t)cta * 11008), "r"(11008) : "memory");
        asm volatile("cp.async.bulk.wait_group 0;" ::: "memory");
        TLW(55);
        flag_signal(FL_U + nb, 2);
        TLW(56);
      }
      __syncwarp();
      sts128(sb + OFF_UT + (lane >> 3) * UT_CH + ((lane >> 2) & 1) * UT_PAR + 2048 + (lane & 3) * 16, 0, 0, 0, 0);
      fence_async_smem();
      __syncwarp();
      if (elect()) {
        flag_wait(FL_U + (cta >> 4), target);
        mbar_expect(sb + B_UFULL, 16384);
#pragma unroll 1
        for (int i = 0; i < 8; i++)
          bulk_load(sb + ut_off(i & 3) + (i >> 2) * UT_PAR, g_u + ((size_t)(i >> 2) * 512 + 4 * cta + (i & 3)) * 2048, 2048, sb + B_UFULL);
        TLW(57);
      }
      __syncwarp();
      mbar_wait(sb + B_G1DONE, 0);
      flag_wait(FL_H + (HGROUP ? cta >> 4 : tb), target);
      TLW(39);
      const uint8_t* hsrc = g_h + (size_t)tb * 88 * 2048;
#pragma unroll 1
      for (int st = 0; st < 22; st++) {
        const uint32_t slot = st & 7;
        if (st == 6 || st == 7) mbar_wait(sb + B_C01 + 8 * (st - 6), 0);
        else if (st > 7) mbar_wait(sb + B_EMPTY2 + 8 * slot, (st >> 4) & 1);
        if (elect()) {
          const uint32_t bar = sb + B_FULL2 + 8 * slot;
          mbar_expect(bar, 8192);
          bulk_load(sb + h_slot(slot), hsrc + st * 8192, 8192, bar);
        }
        __syncwarp();
      }
    } else if (w4 == 2) {
      nb_sync(NB_H0, 160);
      if (lane == 0) flag_signal(FL_H + (HGROUP ? 2 * (mb >> 2) : 2 * mb), HGROUP ? 1 : 4);
      __syncwarp();
      TLW(60);
      nb_sync(NB_G, 160);
      if (lane == 0) flag_signal(FL_G + mb, 4);
      __syncwarp();
      TLW(58);
      const uint32_t target = lds32(sb + OFF_EPOCH);
      if (elect()) {
        mbar_expect(sb + B_YFULL, 16384 + 256);
        flag_wait(FL_G + (tb >> 1), target);
        bulk_load(sb + OFF_GATE, g_gate + 64 * tb, 256, sb + B_YFULL);
        TLW(62);
      }
      __syncwarp();
      mbar_wait(sb + B_PEMPTY + 24, 0);
      if (elect()) {
        flag_wait(FL_Y + cq, target);
        bulk_load(sb + OFF_P, g_y + ((size_t)tb * 512 + 128 * cq) * 128, 16384, sb + B_YFULL);
        TLW(41);
      }
      __syncwarp();
    } else {
      nb_sync(NB_H1, 160);
      if (lane == 0) flag_signal(FL_H + (HGROUP ? 2 * (mb >> 2) : 2 * mb) + 1, HGROUP ? 1 : 4);
      __syncwarp();
      TLW(61);
      mbar_wait(sb + B_DONE, 0);
      return;
    }
    if (lane == 0) mbar_arrive(sb + B_DONE);
  } else if (wg == 2) {
    asm volatile("setmaxnreg.dec.sync.aligned.u32 72;");
    const int tau = threadIdx.x & 127, chi = w4 >> 1, mu = tau & 63;

    uint32_t pla, pai, pcr, pci, pe;
    float pdt;
#pragma unroll
    for (int P = 1; P >= 0; P--) {
      pla = raw[6 * P]; pai = raw[6 * P + 1]; pcr = raw[6 * P + 2]; pci = raw[6 * P + 3];
      const uint32_t m2 = __vmaxu2(__vmaxu2(pcr & 0x7fff7fffu, pci & 0x7fff7fffu), __vmaxu2(raw[6 * P + 4] & 0x7fff7fffu, raw[6 * P + 5] & 0x7fff7fffu));
      pe = min(max(__reduce_max_sync(0xffffffffu, max(m2 & 0xffffu, m2 >> 16)) >> 7, 1u), 253u) << 23 | raw[14 + P];
      pdt = bf_round(expf(bf_lo(raw[12 + P])));
      if (P) {
        sts128(sb + OFF_PARK + 16 * tau, pla, pai, pcr, pci);
        asm volatile("st.shared.v2.u32 [%0], {%1, %2};" ::"r"(sb + OFF_PARK + 2048 + 8 * tau), "r"(pe), "r"(__float_as_uint(pdt)) : "memory");
      }
    }
    TL(50);
    float dk[24];
#pragma unroll 1
    for (int it = 0; it < 4; it++) {
      {
        const float ar = -bf_round(expf(bf_lo(pla)));
        const float a2 = ar * pdt * 1.4426950408889634f, beta = bf_lo(pai) * pdt;
        const uint32_t sa = sb + OFF_KS + chi * 8192 + mu * 16, sbb = sb + OFF_KS + 16384 + chi * 6144 + mu * 16;
        {
          const cf w8 = cpow_seed(a2, -beta, 8.f), w16 = csq(w8), w32 = csq(w16), w64 = csq(w32), w128 = csq(w64), w192 = cmul(w64, w128);
          const float psd = __uint_as_float((254u << 23) - (pe & 0xffff0000u));
          const cf a0 = {bf_lo(pcr) * psd, -bf_lo(pci) * psd};
          const cf a1 = cmul(a0, w8), a2c = cmul(a0, w16), a3 = cmul(a1, w16);
          uint32_t R[4], I[4], r[4], i[4];
          R[0] = pack_f16(a0.r, a1.r); R[1] = pack_f16(a2c.r, a3.r);
          I[0] = pack_f16(a0.i, a1.i); I[1] = pack_f16(a2c.i, a3.i);
          uint32_t wr = pack_f16(w32.r, w32.r), wi = pack_f16(w32.i, w32.i);
          hcmul(R[0], I[0], wr, wi, R[2], I[2]); hcmul(R[1], I[1], wr, wi, R[3], I[3]);
          sts128(sa, R[0], R[1], R[2], R[3]); sts128(sa + 1024, I[0], I[1], I[2], I[3]);
          const cf ws[3] = {w64, w128, w192};
#pragma unroll
          for (int q = 0; q < 3; q++) {
            wr = pack_f16(ws[q].r, ws[q].r); wi = pack_f16(ws[q].i, ws[q].i);
#pragma unroll
            for (int k = 0; k < 4; k++) hcmul(R[k], I[k], wr, wi, r[k], i[k]);
            sts128(sa + 2048 * (q + 1), r[0], r[1], r[2], r[3]); sts128(sa + 2048 * (q + 1) + 1024, i[0], i[1], i[2], i[3]);
          }
        }
        {
          const cf z1 = cpow_seed(a2, beta, 1.f), z2 = csq(z1), z3 = cmul(z2, z1), z4 = csq(z2), z5 = cmul(z4, z1), z6 = csq(z3), z7 = cmul(z4, z3);
          const uint32_t R0 = pack_f16(1.f, z4.r), R1 = pack_f16(z2.r, z6.r), I0 = pack_f16(0.f, z4.i), I1 = pack_f16(z2.i, z6.i);
          sts128(sbb, R0, R1, pack_f16(z1.r, z5.r), pack_f16(z3.r, z7.r));
          sts128(sbb + 1024, I0, I1, pack_f16(z1.i, z5.i), pack_f16(z3.i, z7.i));
          const cf v1 = cpow_seed(a2, beta, 256.f), v2 = csq(v1), v3 = cmul(v2, v1), v4 = csq(v2), v5 = cmul(v4, v1), v6 = csq(v3), v7 = cmul(v4, v3), v8 = csq(v4);
          uint32_t r[4], i[4];
          const uint32_t wr = pack_f16(v1.r, v1.r), wi = pack_f16(v1.i, v1.i);
          hcmul(R0, I0, wr, wi, r[0], i[0]); hcmul(R1, I1, wr, wi, r[1], i[1]);
          hcmul(R0, I0, pack_f16(v2.r, v2.r), pack_f16(v2.i, v2.i), r[2], i[2]);
          hcmul(R0, I0, pack_f16(v3.r, v3.r), pack_f16(v3.i, v3.i), r[3], i[3]);
          sts128(sbb + 2048, r[0], r[1], r[2], r[3]); sts128(sbb + 3072, i[0], i[1], i[2], i[3]);
          sts128(sbb + 4096, pack_f16(v4.r, v5.r), pack_f16(v6.r, v7.r), pack_f16(v8.r, 0.f), 0);
          sts128(sbb + 5120, pack_f16(v4.i, v5.i), pack_f16(v6.i, v7.i), pack_f16(v8.i, 0.f), 0);
        }
      }
      fence_async_smem();
      nb_sync(NB_AUX, 128);
      TL(21 + 3 * it);
      {
        const uint32_t da = ((sd + OFF_KS) >> 4) | (64u << 16), db = da + 1024;
        wg_fence();
#pragma unroll
        for (int k = 0; k < 8; k++) mma_kgen(dk, da + 8 * k, db + 8 * k, (it & 1) | k);
        wg_commit();
        wg_wait<0>();
        pin(dk);
      }
      nb_sync(NB_AUX, 128);
      TL(22 + 3 * it);
      int tid_local = threadIdx.x;
      asm volatile("" : "+r"(tid_local));
      const int lane = tid_local & 31, g = lane >> 2, t = lane & 3, tau = tid_local & 127, mu = tau & 63;
      if (!(it & 1)) {
        pla >>= 16; pai >>= 16; pcr >>= 16; pci >>= 16;
      } else {
        const uint32_t kc = sb + OFF_KS + chi * KC_CH;
        const uint32_t s0 = sb + (it == 1 ? OFF_A : OFF_KT23) + chi * KT_CH + 112;
        {
          const int i0 = 16 * (w4 & 1) + g;
          const float pks = 2.f * pdt * bf_hi(pe);
          float v[12];
#pragma unroll
          for (int k = 0; k < 12; k++) v[k] = (chi ? dk[12 + k] : dk[k]) * pks;
          if (mu == 0) v[0] += bf_lo(pe);
          const uint32_t b = kc + 4 * (t < 2 ? 4 + 4 * i0 + t : 4 + 64 * t + 2 * i0);
          const uint32_t be = t < 2 ? 8 : 4;
          stsf(b, v[4]); stsf(b + be, v[5]); stsf(b + 16 * be, v[6]); stsf(b + 17 * be, v[7]);
          const uint32_t c = kc + 4 * (260 + 64 * t + i0);
          if (t < 2) { stsf(c, v[8]); stsf(c + 128, v[9]); stsf(c + 32, v[10]); stsf(c + 160, v[11]); }
          else if (t == 2 && i0 == 0) stsf(c, v[8]);
          else if (mu == 63) stsf(kc + 12, v[3]);
          const uint32_t a = s0 + 16 * i0 + 2 * ((t & 1) * 2 + (t >> 1));
          const uint32_t e0 = pack_bf16(v[0], v[1]), e1 = pack_bf16(v[2], v[3]);
          sts16(a, e0); sts16(a + 8, e0 >> 16); sts16(a + 128, e1); sts16(a + 136, e1 >> 16);
          sts16(a + KT_COPY + 2, e0); sts16(a + KT_COPY + 10, e0 >> 16); sts16(a + KT_COPY + 130, e1);
          if (mu != 63) sts16(a + KT_COPY + 138, e1 >> 16);
          if (mu < 14) sts128(s0 - 112 + 16 * mu + (mu < 7 ? 0 : KT_COPY - 112), 0, 0, 0, 0);
          else if (mu == 14) sts16(s0 + KT_COPY, 0);
        }
        if (it == 1) {
          const int ii = lane & 7;
          const uint32_t src = sb + OFF_UT + (64 * (w4 & 1) + 7 - ii) * 128 + 16 * ((4 * chi + (lane >> 3)) ^ (7 - ii));
          uint32_t v[32];
          mbar_wait(sb + B_XTFULL, 0);
#pragma unroll
          for (int r = 0; r < 8; r++) ldsm4(src + r * 1024, v + 4 * r);
          nb_sync(NB_AUX, 128);
          const uint32_t ub = sb + OFF_UT + (32 * chi + lane) * 128;
#pragma unroll
          for (int r = 0; r < 8; r++)
            stsm4t(ub + (r & 1) * 8192 + 16 * ((4 * (1 - (w4 & 1)) + (r >> 1)) ^ ii), v[4 * r], v[4 * r + 1], v[4 * r + 2], v[4 * r + 3]);
          fence_async_smem();
          nb_arrive(NB_UT, 160);
          TL(20);
          const float4 np = ldsf4(sb + OFF_PARK + 16 * tau);
          const float2 ns = ldsf2(sb + OFF_PARK + 2048 + 8 * tau);
          pla = __float_as_uint(np.x); pai = __float_as_uint(np.y); pcr = __float_as_uint(np.z); pci = __float_as_uint(np.w);
          pe = __float_as_uint(ns.x); pdt = ns.y;
        } else {
          nb_sync(NB_AUX, 128);
        }
        const bool odd = w4 & 1;
        const float4 a = ldsf4(kc + 16 + 16 * lane);
        float ax = ldsf(odd ? kc + 12 : kc + 32 + 16 * lane);
        const float2 q = ldsf2(kc + 528 + 8 * mu);
        const float q2 = ldsf(kc + 536 + 8 * mu);
        const float r0 = ldsf(kc + 1040 + 4 * mu), r1 = ldsf(kc + 1044 + 4 * mu), r2 = ldsf(kc + 1296 + 4 * mu), r3 = ldsf(kc + 1300 + 4 * mu);
        {
          const uint32_t c22 = pack_bf16(a.z, a.z);
          if (!odd) sts128(s0 + 512 + 16 * lane, pack_bf16(a.x, a.x), pack_bf16(a.y, a.z), c22, pack_bf16(a.w, ax));
          else sts128(s0 + KT_COPY + 512 + 16 * lane, pack_bf16(lane ? a.x : ax, a.x), pack_bf16(a.x, a.y), c22, pack_bf16(a.z, a.w));
        }
        const uint32_t sm0 = s0 + 16 * mu, sm1 = sm0 + KT_COPY;
        {
          const uint32_t c00 = pack_bf16(q.x, q.x), c11 = pack_bf16(q.y, q.y);
          sts128(sm0 + 1024, c00, pack_bf16(q.x, q.y), c11, pack_bf16(q2, q2));
          sts128(sm1 + 1024, c00, c00, c11, pack_bf16(q.y, q2));
        }
#pragma unroll
        for (int k = 0; k < 2; k++) {
          const float pa = k ? r2 : r0, pb = k ? r3 : r1, px = (lane & 1) ? pb : pa;
          const uint32_t caa = pack_bf16(pa, pa), cbb = pack_bf16(pb, pb);
          sts128(sm0 + 2048 + 1024 * k, caa, caa, pack_bf16(px, pb), cbb);
          sts128(sm1 + 2048 + 1024 * k, caa, caa, pack_bf16(pa, px), cbb);
        }
        fence_async_smem();
        if (it == 1) { nb_arrive(NB_TAB01, 256); nb_sync(NB_AUX, 128); }
        else { __syncwarp(); if (lane == 0) mbar_arrive(sb + B_TAB23); }
        TL(23 + 3 * it);
      }
    }

    {
      const int tok = 128 * mb + 16 * nb + 4 * w4;
      const uint4* xr = (const uint4*)(p.x + (size_t)tok * kD) + lane;
      uint4 v[8], gw[2];
#pragma unroll
      for (int k = 0; k < 8; k++) v[k] = __ldg(xr + 32 * k);
      gw[0] = __ldg((const uint4*)p.gate_w + lane); gw[1] = __ldg((const uint4*)p.gate_w + 32 + lane);
      float s[4];
#pragma unroll
      for (int k = 0; k < 8; k++) {
        const uint4 a = v[k], b = gw[k & 1];
        const uint32_t q0 = bmul2(a.x, b.x), q1 = bmul2(a.y, b.y), q2 = bmul2(a.z, b.z), q3 = bmul2(a.w, b.w);
        const float r = ((bf_lo(q0) + bf_hi(q0)) + (bf_lo(q1) + bf_hi(q1))) + ((bf_lo(q2) + bf_hi(q2)) + (bf_lo(q3) + bf_hi(q3)));
        s[k >> 1] = (k & 1) ? s[k >> 1] + r : r;
      }
      const bool b0 = lane & 1, b1 = lane & 2;
      const float u0 = (b0 ? s[1] : s[0]) + __shfl_xor_sync(0xffffffffu, b0 ? s[0] : s[1], 1);
      const float u1 = (b0 ? s[3] : s[2]) + __shfl_xor_sync(0xffffffffu, b0 ? s[2] : s[3], 1);
      float r = (b1 ? u1 : u0) + __shfl_xor_sync(0xffffffffu, b1 ? u0 : u1, 2);
      r += __shfl_xor_sync(0xffffffffu, r, 4);
      r += __shfl_xor_sync(0xffffffffu, r, 8);
      r += __shfl_xor_sync(0xffffffffu, r, 16);
      const float gt = bf_round(1.f / (1.f + expf(-bf_round(r))));
      if (lane < 4) g_gate[tok + lane] = pack_bf16(gt, 1.f - gt);
      nb_arrive(NB_G, 160);
    }
    TL(33);

    {
      const int half = lane >> 4, wd = 16 * (w4 & 1) + (lane & 15), row0 = 16 * (w4 >> 1) + half;
      uint32_t pa[4];
#pragma unroll
      for (int r = 0; r < 4; r++) {
        const int sw = (wd - r) & 31, row = row0 - (wd < r);
        pa[r] = sb + OFF_P + r * 4096 + row * 128 + 16 * ((sw >> 2) ^ r ^ (4 * (row & 1))) + 4 * (sw & 3);
      }
#pragma unroll 1
      for (int c = 0; c < 4; c++) {
        const int ch = 4 * cta + c;
        uint8_t* yo = g_y + ((size_t)row0 * 512 + ch) * 128 + 16 * ((wd >> 2) ^ (ch & 7)) + 4 * (wd & 3);
        nb_sync(c == 2 ? NB_PFULL1 : NB_PFULL0, 256);
        uint32_t o[8];
#pragma unroll
        for (int k = 0; k < 8; k++) {
          uint32_t v0 = lds32(pa[0] + 256 * k), v1 = lds32(pa[1] + 256 * k), v2 = lds32(pa[2] + 256 * k), v3 = lds32(pa[3] + 256 * k);
          if (k == 0 && row0 == 0) { if (wd < 1) v1 = 0; if (wd < 2) v2 = 0; if (wd < 3) v3 = 0; }
          o[k] = badd2(badd2(v0, v1), badd2(v2, v3));
        }
        __syncwarp();
        if (lane == 0) mbar_arrive(sb + B_PEMPTY + 8 * c);
#pragma unroll
        for (int k = 0; k < 8; k++) *(uint32_t*)(yo + (size_t)k * 131072) = o[k];
        TL(34 + c);
      }
      nb_sync(NB_AUX, 128);
      if (tau == 0) flag_signal(FL_Y + (cta >> 5), 1);
      __syncwarp();
    }
    TL(38);
    if (lane == 0) mbar_arrive(sb + B_DONE);
  } else {
    asm volatile("setmaxnreg.inc.sync.aligned.u32 208;");
    if (wg == 0) TL(51);
    {
      float ag[88], au[88];
      uint32_t slot = 0, ph = 0, prev = 0;
#pragma unroll 1
      for (int ks = 0; ks < 16; ks++) {
        if (wg == 1 && ks == 12) {
          wg_wait<0>();
          if (lane == 0) mbar_arrive(sb + B_EMPTY1 + 8 * prev);
          nb_sync(NB_SKEW, 256);
        }
        mbar_wait(sb + B_FULL1 + 8 * slot, ph);
        if (ks == 0) TL(4 + wg);
        if (wg == 0 && ks == 4) TL(52);
        if (wg == 0 && ks == 8) TL(53);
        if (wg == 0 && ks == 12) TL(54);
        const uint32_t base = (sd + slot * SLOT1) >> 4;
        const uint32_t da = (base + wg * 256) | (1u << 16), db = (base + 512) | (256u << 16);
        wg_fence();
        mma_g1(ag, da, db, ks);
        mma_g1(au, da, db + 768, ks);
        mma_g1(ag, da + 2, db + 128, 1);
        mma_g1(au, da + 2, db + 768 + 128, 1);
        wg_commit();
        if (ks == 15) nb_arrive(wg ? NB_C0GO : NB_SKEW, 256);
        wg_wait<1>();
        if (ks > 0 && !(wg == 1 && ks == 12) && lane == 0) mbar_arrive(sb + B_EMPTY1 + 8 * prev);
        prev = slot;
        if (++slot == 5) { slot = 0; ph ^= 1; }
      }
      wg_wait<0>();
      pin(ag); pin(au);
      if (lane == 0) mbar_arrive(sb + B_G1DONE);
      TL(6 + wg);
      uint8_t* hp = g_h + (size_t)(2 * mb + wg) * 88 * 2048 + nb * 8192 + w4 * 256 + lane * 4;
#pragma unroll
      for (int j = 0; j < 22; j++) {
        float h[4];
#pragma unroll
        for (int e = 0; e < 4; e++) {
          const float hg = 0.5f * ag[4 * j + e];
          float th;
          asm("tanh.approx.f32 %0, %1;" : "=f"(th) : "f"(hg));
          const float q = hg * au[4 * j + e];
          h[e] = fmaf(q, th, q);
        }
        if (j == 16) hp -= nb * 2048;
        *(uint32_t*)(hp + (j >> 3) * 65536 + (j & 7) * 1024) = pack_bf16(h[0], h[1]);
        *(uint32_t*)(hp + (j >> 3) * 65536 + (j & 7) * 1024 + 128) = pack_bf16(h[2], h[3]);
      }
      nb_arrive(NB_H0 + wg, 160);
      TL(8 + wg);
    }
    const int mat = lane >> 3, ii = lane & 7;
    {
      const uint32_t pw = sb + OFF_P + (ii & 3) * 4096 + (31 - 2 * (mat >> 1) - (ii >> 2)) * 128 +
                          16 * ((2 * w4 + (mat & 1)) ^ (ii & 3) ^ (4 * (1 - (ii >> 2))));
      mbar_wait(sb + B_UFULL, 0);
#pragma unroll 1
      for (int c = 2 * wg; c < 4; c = 2 * c + 1) {
        if (c == 0) { nb_sync(NB_TAB01, 256); nb_sync(NB_C0GO, 256); }
        else if (c > 1) mbar_wait(sb + B_TAB23, 0);
        const uint32_t ka = sd + (c < 2 ? OFF_A : OFF_KT23) + (c & 1) * KT_CH;
        const uint32_t ua = sd + ut_off(c);
        float d[64];
        wg_fence();
        ConvSeq<0>::run(d, (ka >> 4) | (8u << 16), (ua >> 4) | (4u << 16));
        wg_commit();
        if (c == 3) nb_arrive(NB_G2GO, 256);
        wg_wait<0>();
        pin(d);
        TL(10 + 2 * c);
        if ((c == 1 || c == 2) && lane == 0) mbar_arrive(sb + B_C01 + 8 * (c - 1));
        mbar_wait(sb + (c == 0 ? B_G1DONE : B_PEMPTY + 8 * (c - 1)), 0);
#pragma unroll
        for (int q = 0; q < 8; q++)
          stsm4t(pw - 512 * q, pack_bf16(d[8 * q], d[8 * q + 1]), pack_bf16(d[8 * q + 2], d[8 * q + 3]),
                 pack_bf16(d[8 * q + 4], d[8 * q + 5]), pack_bf16(d[8 * q + 6], d[8 * q + 7]));
        nb_arrive(NB_PFULL0 + wg, 256);
        TL(11 + 2 * c);
      }
    }
    if (wg == 1) {
      float d[64];
      auto g2_stage = [&](int st, int nk) {
        const uint32_t slot = st & 7;
        const uint32_t da = ((sd + h_slot(slot)) >> 4) | (64u << 16), db = ((sd + w_slot(slot)) >> 4) | (512u << 16);
        wg_fence();
        mma_g2(d, da, db, st);
        mma_g2(d, da + 128, db + 128, 1);
        if (nk == 4) { mma_g2(d, da + 256, db + 256, 1); mma_g2(d, da + 384, db + 384, 1); }
        wg_commit();
      };
      mbar_wait(sb + B_FULL2, 0);
      TL(40);
      nb_sync(NB_G2GO, 256);
#pragma unroll 1
      for (int st = 0; st < 19; st++) {
        g2_stage(st, 4);
        const uint32_t nbar = sb + B_FULL2 + 8 * ((st + 1) & 7), npar = ((st + 1) >> 3) & 1;
        const bool ready = mbar_test(nbar, npar);
        wg_wait<1>();
        if (st > 0 && lane == 0) mbar_arrive(sb + B_EMPTY2 + 8 * ((st - 1) & 7));
        if (!ready) mbar_wait(nbar, npar);
        if (!(st & 1)) TL(96 + st);
      }
      g2_stage(19, 4);
      mbar_wait(sb + B_FULL2 + 8 * 4, 0);
      mbar_wait(sb + B_YFULL, 0);
      TL(18);
      const uint32_t ga = lds32(sb + OFF_GATE + 4 * (16 * w4 + (lane >> 2))), gb = lds32(sb + OFF_GATE + 4 * (16 * w4 + (lane >> 2)) + 32);
      const uint32_t ya = sb + OFF_P + (8 * (mat >> 1) + ii) * 128 + 16 * ((2 * w4 + (mat & 1)) ^ ii);
      uint32_t yv[32];
#pragma unroll
      for (int jj = 0; jj < 4; jj++) ldsm4t(ya + jj * 2048, yv + 4 * jj);
      g2_stage(20, 4);
      mbar_wait(sb + B_FULL2 + 8 * 5, 0);
#pragma unroll
      for (int jj = 4; jj < 8; jj++) ldsm4t(ya + jj * 2048, yv + 4 * jj);
      g2_stage(21, 2);
      TL(44);
      mbar_wait(sb + B_EMPTY2 + 8 * 6, 1);
      const uint32_t g0 = __byte_perm(ga, 0, 0x1010), g1 = __byte_perm(gb, 0, 0x1010);
      const uint32_t o0 = __byte_perm(ga, 0, 0x3232), o1 = __byte_perm(gb, 0, 0x3232);
#pragma unroll
      for (int e = 0; e < 32; e++) yv[e] = bmul2((e & 1) ? g1 : g0, yv[e]);
      wg_wait<0>();
      pin(d);
      TL(45);
      const uint32_t oa = sb + OFF_A + w4 * 4096 + (ii + 8 * (mat & 1)) * 128;
#pragma unroll
      for (int jj = 0; jj < 8; jj++) {
#pragma unroll
        for (int e = 0; e < 4; e++)
          yv[4 * jj + e] = bfma2((e & 1) ? o1 : o0, pack_bf16(d[8 * jj + 2 * e], d[8 * jj + 2 * e + 1]), yv[4 * jj + e]);
        stsm4(oa + (jj >> 2) * 2048 + 16 * ((2 * (jj & 3) + (mat >> 1)) ^ ii), yv[4 * jj], yv[4 * jj + 1], yv[4 * jj + 2], yv[4 * jj + 3]);
      }
      fence_async_smem();
      __syncwarp();
      if (elect()) {
        tma3d_store(&tm_out, sb + OFF_A + w4 * 4096, 0, 64 * tb + 16 * w4, 2 * cq);
        asm volatile("cp.async.bulk.commit_group;" ::: "memory");
        asm volatile("cp.async.bulk.wait_group.read 0;" ::: "memory");
      }
      __syncwarp();
      TL(46);
    }
    if (lane == 0) mbar_arrive(sb + B_DONE);
  }
}

typedef CUresult (*EncodeFn)(CUtensorMap*, CUtensorMapDataType, cuuint32_t, void*, const cuuint64_t*, const cuuint64_t*,
                             const cuuint32_t*, const cuuint32_t*, CUtensorMapInterleave, CUtensorMapSwizzle,
                             CUtensorMapL2promotion, CUtensorMapFloatOOBfill);

static void encode(EncodeFn fn, CUtensorMap* m, const void* base, int rank, const cuuint64_t* dims, const cuuint64_t* strides,
                   const cuuint32_t* box, CUtensorMapSwizzle sw) {
  const cuuint32_t es[4] = {1, 1, 1, 1};
  fn(m, CU_TENSOR_MAP_DATA_TYPE_BFLOAT16, rank, const_cast<void*>(base), dims, strides, box, es, CU_TENSOR_MAP_INTERLEAVE_NONE, sw,
     CU_TENSOR_MAP_L2_PROMOTION_L2_128B, CU_TENSOR_MAP_FLOAT_OOB_FILL_NONE);
}

extern "C" void kernel_launch(void* const* d_in, const int* in_sizes, int n_in, void* d_out, int out_size) {
  void* fp = nullptr;
  cudaDriverEntryPointQueryResult qr;
  cudaGetDriverEntryPoint("cuTensorMapEncodeTiled", &fp, cudaEnableDefault, &qr);
  EncodeFn fn = (EncodeFn)fp;
  CUtensorMap tm_x, tm_wg, tm_wu, tm_wd, tm_out, tm_u, tm_xp;
  {
    const cuuint64_t dims[2] = {kD, kL}, st[1] = {kD * 2};
    const cuuint32_t box[2] = {32, 128};
    encode(fn, &tm_x, d_in[0], 2, dims, st, box, CU_TENSOR_MAP_SWIZZLE_64B);
  }
  {
    const cuuint64_t dims[2] = {kF, kD}, st[1] = {kF * 2};
    const cuuint32_t box[2] = {64, 32};
    encode(fn, &tm_wg, d_in[8], 2, dims, st, box, CU_TENSOR_MAP_SWIZZLE_128B);
    encode(fn, &tm_wu, d_in[9], 2, dims, st, box, CU_TENSOR_MAP_SWIZZLE_128B);
  }
  {
    const cuuint64_t st[2] = {kD * 2, 128};
    const cuuint32_t box[3] = {64, 64, 2};
    const cuuint64_t dw[3] = {64, kF, 8}, dx[3] = {64, kL, 8};
    encode(fn, &tm_wd, d_in[10], 3, dw, st, box, CU_TENSOR_MAP_SWIZZLE_128B);
    const cuuint32_t boxo[3] = {64, 16, 2};
    encode(fn, &tm_out, d_out, 3, dx, st, boxo, CU_TENSOR_MAP_SWIZZLE_128B);
  }
  {
    void* u = nullptr;
    cudaGetSymbolAddress(&u, g_u);
    const cuuint64_t dims[3] = {1024, 512, 2}, st[2] = {2048, 512 * 2048};
    const cuuint32_t box[3] = {64, 64, 2};
    encode(fn, &tm_u, u, 3, dims, st, box, CU_TENSOR_MAP_SWIZZLE_128B);
  }
  {
    const cuuint64_t dims[4] = {kD, 8, 8, 32}, st[3] = {8 * kD * 2, kD * 2, 64 * kD * 2};
    const cuuint32_t box[4] = {64, 8, 8, 2};
    encode(fn, &tm_xp, d_in[0], 4, dims, st, box, CU_TENSOR_MAP_SWIZZLE_128B);
  }
  Params p;
  p.x = (const __nv_bfloat16*)d_in[0];      p.log_a = (const __nv_bfloat16*)d_in[1];
  p.a_im = (const __nv_bfloat16*)d_in[2];   p.c_re = (const __nv_bfloat16*)d_in[3];
  p.c_im = (const __nv_bfloat16*)d_in[4];   p.log_dt = (const __nv_bfloat16*)d_in[5];
  p.d_skip = (const __nv_bfloat16*)d_in[6]; p.w_down = (const __nv_bfloat16*)d_in[10];
  p.gate_w = (const __nv_bfloat16*)d_in[11];
  p.w_gate = (const __nv_bfloat16*)d_in[8]; p.w_up = (const __nv_bfloat16*)d_in[9];
  cudaFuncSetAttribute(gated_mix_kernel, cudaFuncAttributeMaxDynamicSharedMemorySize, SMEM_BYTES);
  gated_mix_kernel<<<128, 512, SMEM_BYTES>>>(tm_x, tm_wg, tm_wu, tm_wd, tm_out, tm_u, tm_xp, p);
}
```

```cpp
#include <cuda_runtime.h>
#include <cuda_bf16.h>
#include <cuda_fp16.h>
#include <cuda.h>
#include <stdint.h>

#define HEAD_STAGES 1
#define EHOLD 1
#define EPI_GROUP 7
#define KB1 8
#define G1SPLIT 2
#define YFIRST 8
#define CONV_ORDER 0
#define PF_MULT 2
#define G1MAP 1
#define SKEWQ 1

namespace {

constexpr int kL = 2048, kD = 512, kF = 1376;

constexpr uint32_t SLOT1   = 32768;
constexpr uint32_t OFF_P   = 0;
constexpr uint32_t OFF_W2  = 16384;
constexpr uint32_t OFF_RECV = OFF_W2 + 5 * 16384;
constexpr uint32_t OFF_HE  = 114688;
constexpr uint32_t OFF_A   = 163840;
constexpr uint32_t KT_COPY = 4208;
constexpr uint32_t KT_CH   = 2 * KT_COPY;
constexpr uint32_t OFF_PARK = OFF_A + 16896;
constexpr uint32_t OFF_KS  = OFF_A + 21504;
constexpr uint32_t OFF_KT23 = OFF_KS + 11840;
constexpr uint32_t OFF_GATE = OFF_A + 40960;
constexpr uint32_t KC_CH   = 2048;
constexpr uint32_t UT_PAR  = 2176;
constexpr uint32_t UT_CH   = 2 * UT_PAR;
constexpr uint32_t OFF_UT  = OFF_KS + 28672;
constexpr uint32_t OFF_HL5 = OFF_UT + UT_CH;
constexpr uint32_t OFF_BAR = OFF_UT + 4 * UT_CH;
constexpr uint32_t OFF_TL  = OFF_BAR + 512;
constexpr uint32_t SMEM_BYTES = OFF_TL + 512;

constexpr uint32_t B_FULL1 = OFF_BAR;
constexpr uint32_t B_EMPTY1 = B_FULL1 + 40, B_G1DONE = B_EMPTY1 + 40;
constexpr uint32_t B_EMPTYW = B_G1DONE + 8, B_SENDOK = B_EMPTYW + 40, B_C12 = B_SENDOK + 8;
constexpr uint32_t B_EMPTYH = B_C12 + 8, B_PEMPTY = B_EMPTYH + 40, B_TAB = B_PEMPTY + 32;
constexpr uint32_t B_SENT = B_TAB + 16;
constexpr uint32_t B_FULL3 = B_SENT + 8;
constexpr uint32_t B_YFULL = B_FULL3 + 40, B_DONE = B_YFULL + 8;
constexpr uint32_t B_HL = B_DONE + 8, B_HE = B_HL + 48, B_WF = B_HE + 48, B_KH = B_WF + 8;
constexpr uint32_t B_UFULL = B_KH + 8, B_XTFULL = B_UFULL + 8, B_RECV = B_XTFULL + 8, B_XTREAD = B_RECV + 8;
constexpr uint32_t B_W5 = B_XTREAD + 8, OFF_EPOCH = B_W5 + 8;
static_assert(OFF_EPOCH + 4 <= OFF_TL && SMEM_BYTES <= 232448 && OFF_UT % 1024 == 0, "shared memory map");

__host__ __device__ constexpr int conv_ch(int c) { return (c + 1) & 3; }

enum { NB_SKEW = 1, NB_H0, NB_H1, NB_GO0, NB_GO1, NB_PFULL0, NB_PFULL1, NB_AUX, NB_UT, NB_KC0, NB_SENT };

constexpr int FLAG_STRIDE = 32;
constexpr int FL_H = 0, FL_U = 32, FL_Y = 40, FL_G = 44;

}

__device__ __align__(1024) uint8_t g_h[32 * 88 * 2048];
__device__ __align__(1024) uint8_t g_y[32 * 512 * 128];
__device__ __align__(1024) uint8_t g_u[2 * 512 * 2048];
__device__ __align__(256) uint32_t g_gate[kL];
__device__ uint32_t g_flags[60 * FLAG_STRIDE];
#define TL(id)
#define TLW(id)
#define TLK(id)
#define TLR(k)
#define TLR_DECL
#define TLR_DUMP
#define TLQ(v)
#define TLS(id, v)
#define XT(k)

namespace {

__device__ __forceinline__ void mma_x(float (&d)[36], uint32_t alo, uint32_t blo, int scale) {
  asm volatile("{\n.reg .pred p;\n.reg .b64 da, db;\nsetp.ne.b32 p, %38, 0;\nmov.b64 da, {%36, %39};\nmov.b64 db, {%37, %40};\n"
    "wgmma.mma_async.sync.aligned.m64n72k16.f32.bf16.bf16 {%0,%1,%2,%3,%4,%5,%6,%7,%8,%9,%10,%11,%12,%13,%14,%15,%16,%17,%18,%19,%20,%21,%22,%23,%24,%25,%26,%27,%28,%29,%30,%31,%32,%33,%34,%35}, da, db, p, 1, 1, 0, 1;\n}\n"
    : "+f"(d[0]),"+f"(d[1]),"+f"(d[2]),"+f"(d[3]),"+f"(d[4]),"+f"(d[5]),"+f"(d[6]),"+f"(d[7]),"+f"(d[8]),"+f"(d[9]),"+f"(d[10]),"+f"(d[11]),"+f"(d[12]),"+f"(d[13]),"+f"(d[14]),"+f"(d[15]),"+f"(d[16]),"+f"(d[17]),"+f"(d[18]),"+f"(d[19]),"+f"(d[20]),"+f"(d[21]),"+f"(d[22]),"+f"(d[23]),"+f"(d[24]),"+f"(d[25]),"+f"(d[26]),"+f"(d[27]),"+f"(d[28]),"+f"(d[29]),"+f"(d[30]),"+f"(d[31]),"+f"(d[32]),"+f"(d[33]),"+f"(d[34]),"+f"(d[35])
    : "r"(alo), "r"(blo), "r"(scale), "n"(-2147483616), "n"(513));
}
__device__ __forceinline__ void mma_g1(float (&d)[84], uint32_t alo, uint32_t blo, int scale) {
  asm volatile("{\n.reg .pred p;\n.reg .b64 da, db;\nsetp.ne.b32 p, %86, 0;\nmov.b64 da, {%84, %87};\nmov.b64 db, {%85, %88};\n"
    "wgmma.mma_async.sync.aligned.m64n168k16.f32.bf16.bf16 {%0,%1,%2,%3,%4,%5,%6,%7,%8,%9,%10,%11,%12,%13,%14,%15,%16,%17,%18,%19,%20,%21,%22,%23,%24,%25,%26,%27,%28,%29,%30,%31,%32,%33,%34,%35,%36,%37,%38,%39,%40,%41,%42,%43,%44,%45,%46,%47,%48,%49,%50,%51,%52,%53,%54,%55,%56,%57,%58,%59,%60,%61,%62,%63,%64,%65,%66,%67,%68,%69,%70,%71,%72,%73,%74,%75,%76,%77,%78,%79,%80,%81,%82,%83}, da, db, p, 1, 1, 0, 1;\n}\n"
    : "+f"(d[0]),"+f"(d[1]),"+f"(d[2]),"+f"(d[3]),"+f"(d[4]),"+f"(d[5]),"+f"(d[6]),"+f"(d[7]),"+f"(d[8]),"+f"(d[9]),"+f"(d[10]),"+f"(d[11]),"+f"(d[12]),"+f"(d[13]),"+f"(d[14]),"+f"(d[15]),"+f"(d[16]),"+f"(d[17]),"+f"(d[18]),"+f"(d[19]),"+f"(d[20]),"+f"(d[21]),"+f"(d[22]),"+f"(d[23]),"+f"(d[24]),"+f"(d[25]),"+f"(d[26]),"+f"(d[27]),"+f"(d[28]),"+f"(d[29]),"+f"(d[30]),"+f"(d[31]),"+f"(d[32]),"+f"(d[33]),"+f"(d[34]),"+f"(d[35]),"+f"(d[36]),"+f"(d[37]),"+f"(d[38]),"+f"(d[39]),"+f"(d[40]),"+f"(d[41]),"+f"(d[42]),"+f"(d[43]),"+f"(d[44]),"+f"(d[45]),"+f"(d[46]),"+f"(d[47]),"+f"(d[48]),"+f"(d[49]),"+f"(d[50]),"+f"(d[51]),"+f"(d[52]),"+f"(d[53]),"+f"(d[54]),"+f"(d[55]),"+f"(d[56]),"+f"(d[57]),"+f"(d[58]),"+f"(d[59]),"+f"(d[60]),"+f"(d[61]),"+f"(d[62]),"+f"(d[63]),"+f"(d[64]),"+f"(d[65]),"+f"(d[66]),"+f"(d[67]),"+f"(d[68]),"+f"(d[69]),"+f"(d[70]),"+f"(d[71]),"+f"(d[72]),"+f"(d[73]),"+f"(d[74]),"+f"(d[75]),"+f"(d[76]),"+f"(d[77]),"+f"(d[78]),"+f"(d[79]),"+f"(d[80]),"+f"(d[81]),"+f"(d[82]),"+f"(d[83])
    : "r"(alo), "r"(blo), "r"(scale), "n"(-2147483616), "n"(1073741888));
}
__device__ __forceinline__ void mma_g2(float (&d)[64], uint32_t alo, uint32_t blo, int scale) {
  asm volatile("{\n.reg .pred p;\n.reg .b64 da, db;\nsetp.ne.b32 p, %66, 0;\nmov.b64 da, {%64, %67};\nmov.b64 db, {%65, %68};\n"
    "wgmma.mma_async.sync.aligned.m64n128k16.f32.bf16.bf16 {%0,%1,%2,%3,%4,%5,%6,%7,%8,%9,%10,%11,%12,%13,%14,%15,%16,%17,%18,%19,%20,%21,%22,%23,%24,%25,%26,%27,%28,%29,%30,%31,%32,%33,%34,%35,%36,%37,%38,%39,%40,%41,%42,%43,%44,%45,%46,%47,%48,%49,%50,%51,%52,%53,%54,%55,%56,%57,%58,%59,%60,%61,%62,%63}, da, db, p, 1, 1, 0, 1;\n}\n"
    : "+f"(d[0]),"+f"(d[1]),"+f"(d[2]),"+f"(d[3]),"+f"(d[4]),"+f"(d[5]),"+f"(d[6]),"+f"(d[7]),"+f"(d[8]),"+f"(d[9]),"+f"(d[10]),"+f"(d[11]),"+f"(d[12]),"+f"(d[13]),"+f"(d[14]),"+f"(d[15]),"+f"(d[16]),"+f"(d[17]),"+f"(d[18]),"+f"(d[19]),"+f"(d[20]),"+f"(d[21]),"+f"(d[22]),"+f"(d[23]),"+f"(d[24]),"+f"(d[25]),"+f"(d[26]),"+f"(d[27]),"+f"(d[28]),"+f"(d[29]),"+f"(d[30]),"+f"(d[31]),"+f"(d[32]),"+f"(d[33]),"+f"(d[34]),"+f"(d[35]),"+f"(d[36]),"+f"(d[37]),"+f"(d[38]),"+f"(d[39]),"+f"(d[40]),"+f"(d[41]),"+f"(d[42]),"+f"(d[43]),"+f"(d[44]),"+f"(d[45]),"+f"(d[46]),"+f"(d[47]),"+f"(d[48]),"+f"(d[49]),"+f"(d[50]),"+f"(d[51]),"+f"(d[52]),"+f"(d[53]),"+f"(d[54]),"+f"(d[55]),"+f"(d[56]),"+f"(d[57]),"+f"(d[58]),"+f"(d[59]),"+f"(d[60]),"+f"(d[61]),"+f"(d[62]),"+f"(d[63])
    : "r"(alo), "r"(blo), "r"(scale), "n"(8), "n"(1073741888));
}
__device__ __forceinline__ void mma_kgen(float (&d)[24], uint32_t alo, uint32_t blo, int scale) {
  asm volatile("{\n.reg .pred p;\n.reg .b64 da, db;\nsetp.ne.b32 p, %26, 0;\nmov.b64 da, {%24, %27};\nmov.b64 db, {%25, %28};\n"
    "wgmma.mma_async.sync.aligned.m64n48k16.f32.f16.f16 {%0,%1,%2,%3,%4,%5,%6,%7,%8,%9,%10,%11,%12,%13,%14,%15,%16,%17,%18,%19,%20,%21,%22,%23}, da, db, p, 1, 1, 1, 1;\n}\n"
    : "+f"(d[0]),"+f"(d[1]),"+f"(d[2]),"+f"(d[3]),"+f"(d[4]),"+f"(d[5]),"+f"(d[6]),"+f"(d[7]),"+f"(d[8]),"+f"(d[9]),"+f"(d[10]),"+f"(d[11]),"+f"(d[12]),"+f"(d[13]),"+f"(d[14]),"+f"(d[15]),"+f"(d[16]),"+f"(d[17]),"+f"(d[18]),"+f"(d[19]),"+f"(d[20]),"+f"(d[21]),"+f"(d[22]),"+f"(d[23])
    : "r"(alo), "r"(blo), "r"(scale), "n"(128), "n"(128));
}
template<int N> __device__ __forceinline__ void mma_conv(float (&d)[64], uint32_t alo, uint32_t blo, int scale);
template<> __device__ __forceinline__ void mma_conv<8>(float (&d)[64], uint32_t alo, uint32_t blo, int scale) {
  asm volatile("{\n.reg .pred p;\n.reg .b64 da, db;\nsetp.ne.b32 p, %6, 0;\nmov.b64 da, {%4, %7};\nmov.b64 db, {%5, %8};\n"
    "wgmma.mma_async.sync.aligned.m64n8k16.f32.bf16.bf16 {%0,%1,%2,%3}, da, db, p, 1, 1, 1, 0;\n}\n"
    : "+f"(d[0]),"+f"(d[1]),"+f"(d[2]),"+f"(d[3])
    : "r"(alo), "r"(blo), "r"(scale), "n"(1), "n"(8));
}
template<> __device__ __forceinline__ void mma_conv<16>(float (&d)[64], uint32_t alo, uint32_t blo, int scale) {
  asm volatile("{\n.reg .pred p;\n.reg .b64 da, db;\nsetp.ne.b32 p, %10, 0;\nmov.b64 da, {%8, %11};\nmov.b64 db, {%9, %12};\n"
    "wgmma.mma_async.sync.aligned.m64n16k16.f32.bf16.bf16 {%0,%1,%2,%3,%4,%5,%6,%7}, da, db, p, 1, 1, 1, 0;\n}\n"
    : "+f"(d[0]),"+f"(d[1]),"+f"(d[2]),"+f"(d[3]),"+f"(d[4]),"+f"(d[5]),"+f"(d[6]),"+f"(d[7])
    : "r"(alo), "r"(blo), "r"(scale), "n"(1), "n"(8));
}
template<> __device__ __forceinline__ void mma_conv<24>(float (&d)[64], uint32_t alo, uint32_t blo, int scale) {
  asm volatile("{\n.reg .pred p;\n.reg .b64 da, db;\nsetp.ne.b32 p, %14, 0;\nmov.b64 da, {%12, %15};\nmov.b64 db, {%13, %16};\n"
    "wgmma.mma_async.sync.aligned.m64n24k16.f32.bf16.bf16 {%0,%1,%2,%3,%4,%5,%6,%7,%8,%9,%10,%11}, da, db, p, 1, 1, 1, 0;\n}\n"
    : "+f"(d[0]),"+f"(d[1]),"+f"(d[2]),"+f"(d[3]),"+f"(d[4]),"+f"(d[5]),"+f"(d[6]),"+f"(d[7]),"+f"(d[8]),"+f"(d[9]),"+f"(d[10]),"+f"(d[11])
    : "r"(alo), "r"(blo), "r"(scale), "n"(1), "n"(8));
}
template<> __device__ __forceinline__ void mma_conv<32>(float (&d)[64], uint32_t alo, uint32_t blo, int scale) {
  asm volatile("{\n.reg .pred p;\n.reg .b64 da, db;\nsetp.ne.b32 p, %18, 0;\nmov.b64 da, {%16, %19};\nmov.b64 db, {%17, %20};\n"
    "wgmma.mma_async.sync.aligned.m64n32k16.f32.bf16.bf16 {%0,%1,%2,%3,%4,%5,%6,%7,%8,%9,%10,%11,%12,%13,%14,%15}, da, db, p, 1, 1, 1, 0;\n}\n"
    : "+f"(d[0]),"+f"(d[1]),"+f"(d[2]),"+f"(d[3]),"+f"(d[4]),"+f"(d[5]),"+f"(d[6]),"+f"(d[7]),"+f"(d[8]),"+f"(d[9]),"+f"(d[10]),"+f"(d[11]),"+f"(d[12]),"+f"(d[13]),"+f"(d[14]),"+f"(d[15])
    : "r"(alo), "r"(blo), "r"(scale), "n"(1), "n"(8));
}
template<> __device__ __forceinline__ void mma_conv<40>(float (&d)[64], uint32_t alo, uint32_t blo, int scale) {
  asm volatile("{\n.reg .pred p;\n.reg .b64 da, db;\nsetp.ne.b32 p, %22, 0;\nmov.b64 da, {%20, %23};\nmov.b64 db, {%21, %24};\n"
    "wgmma.mma_async.sync.aligned.m64n40k16.f32.bf16.bf16 {%0,%1,%2,%3,%4,%5,%6,%7,%8,%9,%10,%11,%12,%13,%14,%15,%16,%17,%18,%19}, da, db, p, 1, 1, 1, 0;\n}\n"
    : "+f"(d[0]),"+f"(d[1]),"+f"(d[2]),"+f"(d[3]),"+f"(d[4]),"+f"(d[5]),"+f"(d[6]),"+f"(d[7]),"+f"(d[8]),"+f"(d[9]),"+f"(d[10]),"+f"(d[11]),"+f"(d[12]),"+f"(d[13]),"+f"(d[14]),"+f"(d[15]),"+f"(d[16]),"+f"(d[17]),"+f"(d[18]),"+f"(d[19])
    : "r"(alo), "r"(blo), "r"(scale), "n"(1), "n"(8));
}
template<> __device__ __forceinline__ void mma_conv<48>(float (&d)[64], uint32_t alo, uint32_t blo, int scale) {
  asm volatile("{\n.reg .pred p;\n.reg .b64 da, db;\nsetp.ne.b32 p, %26, 0;\nmov.b64 da, {%24, %27};\nmov.b64 db, {%25, %28};\n"
    "wgmma.mma_async.sync.aligned.m64n48k16.f32.bf16.bf16 {%0,%1,%2,%3,%4,%5,%6,%7,%8,%9,%10,%11,%12,%13,%14,%15,%16,%17,%18,%19,%20,%21,%22,%23}, da, db, p, 1, 1, 1, 0;\n}\n"
    : "+f"(d[0]),"+f"(d[1]),"+f"(d[2]),"+f"(d[3]),"+f"(d[4]),"+f"(d[5]),"+f"(d[6]),"+f"(d[7]),"+f"(d[8]),"+f"(d[9]),"+f"(d[10]),"+f"(d[11]),"+f"(d[12]),"+f"(d[13]),"+f"(d[14]),"+f"(d[15]),"+f"(d[16]),"+f"(d[17]),"+f"(d[18]),"+f"(d[19]),"+f"(d[20]),"+f"(d[21]),"+f"(d[22]),"+f"(d[23])
    : "r"(alo), "r"(blo), "r"(scale), "n"(1), "n"(8));
}
template<> __device__ __forceinline__ void mma_conv<56>(float (&d)[64], uint32_t alo, uint32_t blo, int scale) {
  asm volatile("{\n.reg .pred p;\n.reg .b64 da, db;\nsetp.ne.b32 p, %30, 0;\nmov.b64 da, {%28, %31};\nmov.b64 db, {%29, %32};\n"
    "wgmma.mma_async.sync.aligned.m64n56k16.f32.bf16.bf16 {%0,%1,%2,%3,%4,%5,%6,%7,%8,%9,%10,%11,%12,%13,%14,%15,%16,%17,%18,%19,%20,%21,%22,%23,%24,%25,%26,%27}, da, db, p, 1, 1, 1, 0;\n}\n"
    : "+f"(d[0]),"+f"(d[1]),"+f"(d[2]),"+f"(d[3]),"+f"(d[4]),"+f"(d[5]),"+f"(d[6]),"+f"(d[7]),"+f"(d[8]),"+f"(d[9]),"+f"(d[10]),"+f"(d[11]),"+f"(d[12]),"+f"(d[13]),"+f"(d[14]),"+f"(d[15]),"+f"(d[16]),"+f"(d[17]),"+f"(d[18]),"+f"(d[19]),"+f"(d[20]),"+f"(d[21]),"+f"(d[22]),"+f"(d[23]),"+f"(d[24]),"+f"(d[25]),"+f"(d[26]),"+f"(d[27])
    : "r"(alo), "r"(blo), "r"(scale), "n"(1), "n"(8));
}
template<> __device__ __forceinline__ void mma_conv<64>(float (&d)[64], uint32_t alo, uint32_t blo, int scale) {
  asm volatile("{\n.reg .pred p;\n.reg .b64 da, db;\nsetp.ne.b32 p, %34, 0;\nmov.b64 da, {%32, %35};\nmov.b64 db, {%33, %36};\n"
    "wgmma.mma_async.sync.aligned.m64n64k16.f32.bf16.bf16 {%0,%1,%2,%3,%4,%5,%6,%7,%8,%9,%10,%11,%12,%13,%14,%15,%16,%17,%18,%19,%20,%21,%22,%23,%24,%25,%26,%27,%28,%29,%30,%31}, da, db, p, 1, 1, 1, 0;\n}\n"
    : "+f"(d[0]),"+f"(d[1]),"+f"(d[2]),"+f"(d[3]),"+f"(d[4]),"+f"(d[5]),"+f"(d[6]),"+f"(d[7]),"+f"(d[8]),"+f"(d[9]),"+f"(d[10]),"+f"(d[11]),"+f"(d[12]),"+f"(d[13]),"+f"(d[14]),"+f"(d[15]),"+f"(d[16]),"+f"(d[17]),"+f"(d[18]),"+f"(d[19]),"+f"(d[20]),"+f"(d[21]),"+f"(d[22]),"+f"(d[23]),"+f"(d[24]),"+f"(d[25]),"+f"(d[26]),"+f"(d[27]),"+f"(d[28]),"+f"(d[29]),"+f"(d[30]),"+f"(d[31])
    : "r"(alo), "r"(blo), "r"(scale), "n"(1), "n"(8));
}
template<> __device__ __forceinline__ void mma_conv<72>(float (&d)[64], uint32_t alo, uint32_t blo, int scale) {
  asm volatile("{\n.reg .pred p;\n.reg .b64 da, db;\nsetp.ne.b32 p, %38, 0;\nmov.b64 da, {%36, %39};\nmov.b64 db, {%37, %40};\n"
    "wgmma.mma_async.sync.aligned.m64n72k16.f32.bf16.bf16 {%0,%1,%2,%3,%4,%5,%6,%7,%8,%9,%10,%11,%12,%13,%14,%15,%16,%17,%18,%19,%20,%21,%22,%23,%24,%25,%26,%27,%28,%29,%30,%31,%32,%33,%34,%35}, da, db, p, 1, 1, 1, 0;\n}\n"
    : "+f"(d[0]),"+f"(d[1]),"+f"(d[2]),"+f"(d[3]),"+f"(d[4]),"+f"(d[5]),"+f"(d[6]),"+f"(d[7]),"+f"(d[8]),"+f"(d[9]),"+f"(d[10]),"+f"(d[11]),"+f"(d[12]),"+f"(d[13]),"+f"(d[14]),"+f"(d[15]),"+f"(d[16]),"+f"(d[17]),"+f"(d[18]),"+f"(d[19]),"+f"(d[20]),"+f"(d[21]),"+f"(d[22]),"+f"(d[23]),"+f"(d[24]),"+f"(d[25]),"+f"(d[26]),"+f"(d[27]),"+f"(d[28]),"+f"(d[29]),"+f"(d[30]),"+f"(d[31]),"+f"(d[32]),"+f"(d[33]),"+f"(d[34]),"+f"(d[35])
    : "r"(alo), "r"(blo), "r"(scale), "n"(1), "n"(8));
}
template<> __device__ __forceinline__ void mma_conv<80>(float (&d)[64], uint32_t alo, uint32_t blo, int scale) {
  asm volatile("{\n.reg .pred p;\n.reg .b64 da, db;\nsetp.ne.b32 p, %42, 0;\nmov.b64 da, {%40, %43};\nmov.b64 db, {%41, %44};\n"
    "wgmma.mma_async.sync.aligned.m64n80k16.f32.bf16.bf16 {%0,%1,%2,%3,%4,%5,%6,%7,%8,%9,%10,%11,%12,%13,%14,%15,%16,%17,%18,%19,%20,%21,%22,%23,%24,%25,%26,%27,%28,%29,%30,%31,%32,%33,%34,%35,%36,%37,%38,%39}, da, db, p, 1, 1, 1, 0;\n}\n"
    : "+f"(d[0]),"+f"(d[1]),"+f"(d[2]),"+f"(d[3]),"+f"(d[4]),"+f"(d[5]),"+f"(d[6]),"+f"(d[7]),"+f"(d[8]),"+f"(d[9]),"+f"(d[10]),"+f"(d[11]),"+f"(d[12]),"+f"(d[13]),"+f"(d[14]),"+f"(d[15]),"+f"(d[16]),"+f"(d[17]),"+f"(d[18]),"+f"(d[19]),"+f"(d[20]),"+f"(d[21]),"+f"(d[22]),"+f"(d[23]),"+f"(d[24]),"+f"(d[25]),"+f"(d[26]),"+f"(d[27]),"+f"(d[28]),"+f"(d[29]),"+f"(d[30]),"+f"(d[31]),"+f"(d[32]),"+f"(d[33]),"+f"(d[34]),"+f"(d[35]),"+f"(d[36]),"+f"(d[37]),"+f"(d[38]),"+f"(d[39])
    : "r"(alo), "r"(blo), "r"(scale), "n"(1), "n"(8));
}
template<> __device__ __forceinline__ void mma_conv<88>(float (&d)[64], uint32_t alo, uint32_t blo, int scale) {
  asm volatile("{\n.reg .pred p;\n.reg .b64 da, db;\nsetp.ne.b32 p, %46, 0;\nmov.b64 da, {%44, %47};\nmov.b64 db, {%45, %48};\n"
    "wgmma.mma_async.sync.aligned.m64n88k16.f32.bf16.bf16 {%0,%1,%2,%3,%4,%5,%6,%7,%8,%9,%10,%11,%12,%13,%14,%15,%16,%17,%18,%19,%20,%21,%22,%23,%24,%25,%26,%27,%28,%29,%30,%31,%32,%33,%34,%35,%36,%37,%38,%39,%40,%41,%42,%43}, da, db, p, 1, 1, 1, 0;\n}\n"
    : "+f"(d[0]),"+f"(d[1]),"+f"(d[2]),"+f"(d[3]),"+f"(d[4]),"+f"(d[5]),"+f"(d[6]),"+f"(d[7]),"+f"(d[8]),"+f"(d[9]),"+f"(d[10]),"+f"(d[11]),"+f"(d[12]),"+f"(d[13]),"+f"(d[14]),"+f"(d[15]),"+f"(d[16]),"+f"(d[17]),"+f"(d[18]),"+f"(d[19]),"+f"(d[20]),"+f"(d[21]),"+f"(d[22]),"+f"(d[23]),"+f"(d[24]),"+f"(d[25]),"+f"(d[26]),"+f"(d[27]),"+f"(d[28]),"+f"(d[29]),"+f"(d[30]),"+f"(d[31]),"+f"(d[32]),"+f"(d[33]),"+f"(d[34]),"+f"(d[35]),"+f"(d[36]),"+f"(d[37]),"+f"(d[38]),"+f"(d[39]),"+f"(d[40]),"+f"(d[41]),"+f"(d[42]),"+f"(d[43])
    : "r"(alo), "r"(blo), "r"(scale), "n"(1), "n"(8));
}
template<> __device__ __forceinline__ void mma_conv<96>(float (&d)[64], uint32_t alo, uint32_t blo, int scale) {
  asm volatile("{\n.reg .pred p;\n.reg .b64 da, db;\nsetp.ne.b32 p, %50, 0;\nmov.b64 da, {%48, %51};\nmov.b64 db, {%49, %52};\n"
    "wgmma.mma_async.sync.aligned.m64n96k16.f32.bf16.bf16 {%0,%1,%2,%3,%4,%5,%6,%7,%8,%9,%10,%11,%12,%13,%14,%15,%16,%17,%18,%19,%20,%21,%22,%23,%24,%25,%26,%27,%28,%29,%30,%31,%32,%33,%34,%35,%36,%37,%38,%39,%40,%41,%42,%43,%44,%45,%46,%47}, da, db, p, 1, 1, 1, 0;\n}\n"
    : "+f"(d[0]),"+f"(d[1]),"+f"(d[2]),"+f"(d[3]),"+f"(d[4]),"+f"(d[5]),"+f"(d[6]),"+f"(d[7]),"+f"(d[8]),"+f"(d[9]),"+f"(d[10]),"+f"(d[11]),"+f"(d[12]),"+f"(d[13]),"+f"(d[14]),"+f"(d[15]),"+f"(d[16]),"+f"(d[17]),"+f"(d[18]),"+f"(d[19]),"+f"(d[20]),"+f"(d[21]),"+f"(d[22]),"+f"(d[23]),"+f"(d[24]),"+f"(d[25]),"+f"(d[26]),"+f"(d[27]),"+f"(d[28]),"+f"(d[29]),"+f"(d[30]),"+f"(d[31]),"+f"(d[32]),"+f"(d[33]),"+f"(d[34]),"+f"(d[35]),"+f"(d[36]),"+f"(d[37]),"+f"(d[38]),"+f"(d[39]),"+f"(d[40]),"+f"(d[41]),"+f"(d[42]),"+f"(d[43]),"+f"(d[44]),"+f"(d[45]),"+f"(d[46]),"+f"(d[47])
    : "r"(alo), "r"(blo), "r"(scale), "n"(1), "n"(8));
}
template<> __device__ __forceinline__ void mma_conv<104>(float (&d)[64], uint32_t alo, uint32_t blo, int scale) {
  asm volatile("{\n.reg .pred p;\n.reg .b64 da, db;\nsetp.ne.b32 p, %54, 0;\nmov.b64 da, {%52, %55};\nmov.b64 db, {%53, %56};\n"
    "wgmma.mma_async.sync.aligned.m64n104k16.f32.bf16.bf16 {%0,%1,%2,%3,%4,%5,%6,%7,%8,%9,%10,%11,%12,%13,%14,%15,%16,%17,%18,%19,%20,%21,%22,%23,%24,%25,%26,%27,%28,%29,%30,%31,%32,%33,%34,%35,%36,%37,%38,%39,%40,%41,%42,%43,%44,%45,%46,%47,%48,%49,%50,%51}, da, db, p, 1, 1, 1, 0;\n}\n"
    : "+f"(d[0]),"+f"(d[1]),"+f"(d[2]),"+f"(d[3]),"+f"(d[4]),"+f"(d[5]),"+f"(d[6]),"+f"(d[7]),"+f"(d[8]),"+f"(d[9]),"+f"(d[10]),"+f"(d[11]),"+f"(d[12]),"+f"(d[13]),"+f"(d[14]),"+f"(d[15]),"+f"(d[16]),"+f"(d[17]),"+f"(d[18]),"+f"(d[19]),"+f"(d[20]),"+f"(d[21]),"+f"(d[22]),"+f"(d[23]),"+f"(d[24]),"+f"(d[25]),"+f"(d[26]),"+f"(d[27]),"+f"(d[28]),"+f"(d[29]),"+f"(d[30]),"+f"(d[31]),"+f"(d[32]),"+f"(d[33]),"+f"(d[34]),"+f"(d[35]),"+f"(d[36]),"+f"(d[37]),"+f"(d[38]),"+f"(d[39]),"+f"(d[40]),"+f"(d[41]),"+f"(d[42]),"+f"(d[43]),"+f"(d[44]),"+f"(d[45]),"+f"(d[46]),"+f"(d[47]),"+f"(d[48]),"+f"(d[49]),"+f"(d[50]),"+f"(d[51])
    : "r"(alo), "r"(blo), "r"(scale), "n"(1), "n"(8));
}
template<> __device__ __forceinline__ void mma_conv<112>(float (&d)[64], uint32_t alo, uint32_t blo, int scale) {
  asm volatile("{\n.reg .pred p;\n.reg .b64 da, db;\nsetp.ne.b32 p, %58, 0;\nmov.b64 da, {%56, %59};\nmov.b64 db, {%57, %60};\n"
    "wgmma.mma_async.sync.aligned.m64n112k16.f32.bf16.bf16 {%0,%1,%2,%3,%4,%5,%6,%7,%8,%9,%10,%11,%12,%13,%14,%15,%16,%17,%18,%19,%20,%21,%22,%23,%24,%25,%26,%27,%28,%29,%30,%31,%32,%33,%34,%35,%36,%37,%38,%39,%40,%41,%42,%43,%44,%45,%46,%47,%48,%49,%50,%51,%52,%53,%54,%55}, da, db, p, 1, 1, 1, 0;\n}\n"
    : "+f"(d[0]),"+f"(d[1]),"+f"(d[2]),"+f"(d[3]),"+f"(d[4]),"+f"(d[5]),"+f"(d[6]),"+f"(d[7]),"+f"(d[8]),"+f"(d[9]),"+f"(d[10]),"+f"(d[11]),"+f"(d[12]),"+f"(d[13]),"+f"(d[14]),"+f"(d[15]),"+f"(d[16]),"+f"(d[17]),"+f"(d[18]),"+f"(d[19]),"+f"(d[20]),"+f"(d[21]),"+f"(d[22]),"+f"(d[23]),"+f"(d[24]),"+f"(d[25]),"+f"(d[26]),"+f"(d[27]),"+f"(d[28]),"+f"(d[29]),"+f"(d[30]),"+f"(d[31]),"+f"(d[32]),"+f"(d[33]),"+f"(d[34]),"+f"(d[35]),"+f"(d[36]),"+f"(d[37]),"+f"(d[38]),"+f"(d[39]),"+f"(d[40]),"+f"(d[41]),"+f"(d[42]),"+f"(d[43]),"+f"(d[44]),"+f"(d[45]),"+f"(d[46]),"+f"(d[47]),"+f"(d[48]),"+f"(d[49]),"+f"(d[50]),"+f"(d[51]),"+f"(d[52]),"+f"(d[53]),"+f"(d[54]),"+f"(d[55])
    : "r"(alo), "r"(blo), "r"(scale), "n"(1), "n"(8));
}
template<> __device__ __forceinline__ void mma_conv<120>(float (&d)[64], uint32_t alo, uint32_t blo, int scale) {
  asm volatile("{\n.reg .pred p;\n.reg .b64 da, db;\nsetp.ne.b32 p, %62, 0;\nmov.b64 da, {%60, %63};\nmov.b64 db, {%61, %64};\n"
    "wgmma.mma_async.sync.aligned.m64n120k16.f32.bf16.bf16 {%0,%1,%2,%3,%4,%5,%6,%7,%8,%9,%10,%11,%12,%13,%14,%15,%16,%17,%18,%19,%20,%21,%22,%23,%24,%25,%26,%27,%28,%29,%30,%31,%32,%33,%34,%35,%36,%37,%38,%39,%40,%41,%42,%43,%44,%45,%46,%47,%48,%49,%50,%51,%52,%53,%54,%55,%56,%57,%58,%59}, da, db, p, 1, 1, 1, 0;\n}\n"
    : "+f"(d[0]),"+f"(d[1]),"+f"(d[2]),"+f"(d[3]),"+f"(d[4]),"+f"(d[5]),"+f"(d[6]),"+f"(d[7]),"+f"(d[8]),"+f"(d[9]),"+f"(d[10]),"+f"(d[11]),"+f"(d[12]),"+f"(d[13]),"+f"(d[14]),"+f"(d[15]),"+f"(d[16]),"+f"(d[17]),"+f"(d[18]),"+f"(d[19]),"+f"(d[20]),"+f"(d[21]),"+f"(d[22]),"+f"(d[23]),"+f"(d[24]),"+f"(d[25]),"+f"(d[26]),"+f"(d[27]),"+f"(d[28]),"+f"(d[29]),"+f"(d[30]),"+f"(d[31]),"+f"(d[32]),"+f"(d[33]),"+f"(d[34]),"+f"(d[35]),"+f"(d[36]),"+f"(d[37]),"+f"(d[38]),"+f"(d[39]),"+f"(d[40]),"+f"(d[41]),"+f"(d[42]),"+f"(d[43]),"+f"(d[44]),"+f"(d[45]),"+f"(d[46]),"+f"(d[47]),"+f"(d[48]),"+f"(d[49]),"+f"(d[50]),"+f"(d[51]),"+f"(d[52]),"+f"(d[53]),"+f"(d[54]),"+f"(d[55]),"+f"(d[56]),"+f"(d[57]),"+f"(d[58]),"+f"(d[59])
    : "r"(alo), "r"(blo), "r"(scale), "n"(1), "n"(8));
}
template<> __device__ __forceinline__ void mma_conv<128>(float (&d)[64], uint32_t alo, uint32_t blo, int scale) {
  asm volatile("{\n.reg .pred p;\n.reg .b64 da, db;\nsetp.ne.b32 p, %66, 0;\nmov.b64 da, {%64, %67};\nmov.b64 db, {%65, %68};\n"
    "wgmma.mma_async.sync.aligned.m64n128k16.f32.bf16.bf16 {%0,%1,%2,%3,%4,%5,%6,%7,%8,%9,%10,%11,%12,%13,%14,%15,%16,%17,%18,%19,%20,%21,%22,%23,%24,%25,%26,%27,%28,%29,%30,%31,%32,%33,%34,%35,%36,%37,%38,%39,%40,%41,%42,%43,%44,%45,%46,%47,%48,%49,%50,%51,%52,%53,%54,%55,%56,%57,%58,%59,%60,%61,%62,%63}, da, db, p, 1, 1, 1, 0;\n}\n"
    : "+f"(d[0]),"+f"(d[1]),"+f"(d[2]),"+f"(d[3]),"+f"(d[4]),"+f"(d[5]),"+f"(d[6]),"+f"(d[7]),"+f"(d[8]),"+f"(d[9]),"+f"(d[10]),"+f"(d[11]),"+f"(d[12]),"+f"(d[13]),"+f"(d[14]),"+f"(d[15]),"+f"(d[16]),"+f"(d[17]),"+f"(d[18]),"+f"(d[19]),"+f"(d[20]),"+f"(d[21]),"+f"(d[22]),"+f"(d[23]),"+f"(d[24]),"+f"(d[25]),"+f"(d[26]),"+f"(d[27]),"+f"(d[28]),"+f"(d[29]),"+f"(d[30]),"+f"(d[31]),"+f"(d[32]),"+f"(d[33]),"+f"(d[34]),"+f"(d[35]),"+f"(d[36]),"+f"(d[37]),"+f"(d[38]),"+f"(d[39]),"+f"(d[40]),"+f"(d[41]),"+f"(d[42]),"+f"(d[43]),"+f"(d[44]),"+f"(d[45]),"+f"(d[46]),"+f"(d[47]),"+f"(d[48]),"+f"(d[49]),"+f"(d[50]),"+f"(d[51]),"+f"(d[52]),"+f"(d[53]),"+f"(d[54]),"+f"(d[55]),"+f"(d[56]),"+f"(d[57]),"+f"(d[58]),"+f"(d[59]),"+f"(d[60]),"+f"(d[61]),"+f"(d[62]),"+f"(d[63])
    : "r"(alo), "r"(blo), "r"(scale), "n"(1), "n"(8));
}

__device__ __forceinline__ void wg_fence() { asm volatile("wgmma.fence.sync.aligned;" ::: "memory"); }
__device__ __forceinline__ void wg_commit() { asm volatile("wgmma.commit_group.sync.aligned;" ::: "memory"); }
template <int N> __device__ __forceinline__ void wg_wait() { asm volatile("wgmma.wait_group.sync.aligned %0;" ::"n"(N) : "memory"); }
template <int N> __device__ __forceinline__ void pin(float (&d)[N]) {
#pragma unroll
  for (int i = 0; i < N; i++) asm volatile("" : "+f"(d[i])::"memory");
}

__device__ __forceinline__ void mbar_init(uint32_t b, int c) { asm volatile("mbarrier.init.shared::cta.b64 [%0], %1;" ::"r"(b), "r"(c) : "memory"); }
__device__ __forceinline__ void mbar_arrive(uint32_t b) { asm volatile("mbarrier.arrive.shared::cta.b64 _, [%0];" ::"r"(b) : "memory"); }
__device__ __forceinline__ void mbar_expect(uint32_t b, uint32_t bytes) { asm volatile("mbarrier.arrive.expect_tx.shared::cta.b64 _, [%0], %1;" ::"r"(b), "r"(bytes) : "memory"); }
__device__ __forceinline__ void mbar_wait(uint32_t b, uint32_t parity) {
  asm volatile(
      "{\n.reg .pred p;\n.reg .u32 n;\n"
      "mbarrier.try_wait.parity.shared::cta.b64 p, [%0], %1;\n@p bra DONE;\nmov.u32 n, 0;\n"
      "W:\nmbarrier.try_wait.parity.shared::cta.b64 p, [%0], %1, 2000;\n@p bra DONE;\n"
      "add.u32 n, n, 1;\nsetp.lt.u32 p, n, 1000000;\n@p bra W;\ntrap;\nDONE:\n}\n" ::"r"(b), "r"(parity) : "memory");
}
__device__ __forceinline__ void cluster_wait() { asm volatile("barrier.cluster.wait.aligned;" ::: "memory"); }
__device__ __forceinline__ void nb_sync(int id, int n) { asm volatile("bar.sync %0, %1;" ::"r"(id), "r"(n) : "memory"); }
__device__ __forceinline__ void nb_arrive(int id, int n) { asm volatile("bar.arrive %0, %1;" ::"r"(id), "r"(n) : "memory"); }
__device__ __forceinline__ void fence_async_smem() { asm volatile("fence.proxy.async.shared::cta;" ::: "memory"); }
__device__ __forceinline__ void fence_async_all() { asm volatile("fence.proxy.async;" ::: "memory"); }

__device__ __forceinline__ void flag_signal(int f, uint32_t inc) {
  fence_async_all();
  asm volatile("red.relaxed.gpu.global.add.u32 [%0], %1;" ::"l"(g_flags + f * FLAG_STRIDE), "r"(inc) : "memory");
}
__device__ __forceinline__ uint32_t flag_peek(const uint32_t* f) {
  uint32_t v;
  asm volatile("ld.relaxed.gpu.global.u32 %0, [%1];" : "=r"(v) : "l"(f) : "memory");
  return v;
}
__device__ __forceinline__ void flag_wait(int idx, uint32_t target) {
  const uint32_t* f = g_flags + idx * FLAG_STRIDE;
#pragma unroll 1
  for (int i = 0; (int32_t)(flag_peek(f) - target) < 0; i++)
    if (i == 20000000) __trap();
  asm volatile("fence.acquire.gpu;" ::: "memory");
  asm volatile("fence.proxy.async.global;" ::: "memory");
}

__device__ __forceinline__ void tma2d(uint32_t dst, const CUtensorMap* m, uint32_t bar, int c0, int c1) {
  asm volatile("cp.async.bulk.tensor.2d.shared::cluster.global.mbarrier::complete_tx::bytes [%0], [%1, {%3, %4}], [%2];"
               ::"r"(dst), "l"(m), "r"(bar), "r"(c0), "r"(c1) : "memory");
}
__device__ __forceinline__ void tma3d(uint32_t dst, const CUtensorMap* m, uint32_t bar, int c0, int c1, int c2) {
  asm volatile("cp.async.bulk.tensor.3d.shared::cluster.global.mbarrier::complete_tx::bytes [%0], [%1, {%3, %4, %5}], [%2];"
               ::"r"(dst), "l"(m), "r"(bar), "r"(c0), "r"(c1), "r"(c2) : "memory");
}
__device__ __forceinline__ void tma2d_pair(uint32_t dst, const CUtensorMap* m, uint32_t bar, int c0, int c1) {
  asm volatile("cp.async.bulk.tensor.2d.shared::cluster.global.mbarrier::complete_tx::bytes.multicast::cluster [%0], [%1, {%3, %4}], [%2], %5;"
               ::"r"(dst), "l"(m), "r"(bar), "r"(c0), "r"(c1), "h"((uint16_t)3) : "memory");
}
__device__ __forceinline__ void tma3d_pair(uint32_t dst, const CUtensorMap* m, uint32_t bar, int c0, int c1, int c2) {
  asm volatile("cp.async.bulk.tensor.3d.shared::cluster.global.mbarrier::complete_tx::bytes.multicast::cluster [%0], [%1, {%3, %4, %5}], [%2], %6;"
               ::"r"(dst), "l"(m), "r"(bar), "r"(c0), "r"(c1), "r"(c2), "h"((uint16_t)3) : "memory");
}
__device__ __forceinline__ void mbar_arrive_cluster(uint32_t b) { asm volatile("mbarrier.arrive.shared::cluster.b64 _, [%0];" ::"r"(b) : "memory"); }
__device__ __forceinline__ void tma4d(uint32_t dst, const CUtensorMap* m, uint32_t bar, int c0, int c1, int c2, int c3) {
  asm volatile("cp.async.bulk.tensor.4d.shared::cluster.global.mbarrier::complete_tx::bytes [%0], [%1, {%3, %4, %5, %6}], [%2];"
               ::"r"(dst), "l"(m), "r"(bar), "r"(c0), "r"(c1), "r"(c2), "r"(c3) : "memory");
}
__device__ __forceinline__ void tma3d_store(const CUtensorMap* m, uint32_t src, int c0, int c1, int c2) {
  asm volatile("cp.async.bulk.tensor.3d.global.shared::cta.bulk_group [%0, {%2, %3, %4}], [%1];"
               ::"l"(m), "r"(src), "r"(c0), "r"(c1), "r"(c2) : "memory");
}
__device__ __forceinline__ void bulk_load(uint32_t dst, const void* src, uint32_t bytes, uint32_t bar) {
  asm volatile("cp.async.bulk.shared::cluster.global.mbarrier::complete_tx::bytes [%0], [%1], %2, [%3];"
               ::"r"(dst), "l"(src), "r"(bytes), "r"(bar) : "memory");
}
__device__ __forceinline__ void cp_async16(uint32_t dst, const void* src) {
  asm volatile("cp.async.cg.shared.global [%0], [%1], 16;" ::"r"(dst), "l"(src) : "memory");
}
__device__ __forceinline__ int selp(int a, int b, bool c) {
  int r;
  asm("{\n.reg .pred p;\nsetp.ne.b32 p, %3, 0;\nselp.b32 %0, %1, %2, p;\n}\n" : "=r"(r) : "r"(a), "r"(b), "r"((int)c));
  return r;
}
template <int FROM, int TO> __device__ __forceinline__ void init_barriers(uint32_t base) {
#pragma unroll
  for (int i = FROM; i < TO; i++) mbar_init(base + 8 * i, i < 5 ? 1 : i < 10 ? 16 : i < 18 ? 8 : i < 30 ? 4 : i < 35 ? 2 : i == 36 ? 15 : 1);
}
__device__ __forceinline__ void sched_fence(uint32_t v, uint32_t other) {
  asm volatile("{\n.reg .pred p;\nsetp.ne.u32 p, %0, %1;\n@p bra OK;\ntrap;\nOK:\n}\n" ::"r"(v), "r"(other) : "memory");
}
__device__ __forceinline__ bool elect() {
  uint32_t p;
  asm volatile("{\n.reg .pred p;\nelect.sync _|p, 0xffffffff;\nselp.b32 %0, 1, 0, p;\n}\n" : "=r"(p));
  return p;
}

__device__ __forceinline__ uint32_t pack_bf16(float lo, float hi) { uint32_t r; asm("cvt.rn.bf16x2.f32 %0, %1, %2;" : "=r"(r) : "f"(hi), "f"(lo)); return r; }
__device__ __forceinline__ uint32_t pack_f16(float lo, float hi) { uint32_t r; asm("cvt.rn.f16x2.f32 %0, %1, %2;" : "=r"(r) : "f"(hi), "f"(lo)); return r; }
__device__ __forceinline__ uint32_t bmul2(uint32_t a, uint32_t b) { uint32_t r; asm("mul.rn.bf16x2 %0, %1, %2;" : "=r"(r) : "r"(a), "r"(b)); return r; }
__device__ __forceinline__ uint32_t badd2(uint32_t a, uint32_t b) { uint32_t r; asm("add.rn.bf16x2 %0, %1, %2;" : "=r"(r) : "r"(a), "r"(b)); return r; }
__device__ __forceinline__ uint32_t bfma2(uint32_t a, uint32_t b, uint32_t c) { uint32_t r; asm("fma.rn.bf16x2 %0, %1, %2, %3;" : "=r"(r) : "r"(a), "r"(b), "r"(c)); return r; }
__device__ __forceinline__ float bf_lo(uint32_t w) { return __uint_as_float(w << 16); }
__device__ __forceinline__ float bf_hi(uint32_t w) { return __uint_as_float(w & 0xffff0000u); }
__device__ __forceinline__ float bf_round(float v) { return __bfloat162float(__float2bfloat16_rn(v)); }

__device__ __forceinline__ void sts128(uint32_t a, uint32_t x, uint32_t y, uint32_t z, uint32_t w) { asm volatile("st.shared.v4.u32 [%0], {%1, %2, %3, %4};" ::"r"(a), "r"(x), "r"(y), "r"(z), "r"(w) : "memory"); }
__device__ __forceinline__ void sts32(uint32_t a, uint32_t x) { asm volatile("st.shared.u32 [%0], %1;" ::"r"(a), "r"(x) : "memory"); }
__device__ __forceinline__ void sts16(uint32_t a, uint32_t x) { asm volatile("st.shared.u16 [%0], %1;" ::"r"(a), "h"((uint16_t)x) : "memory"); }
__device__ __forceinline__ void stsf(uint32_t a, float x) { asm volatile("st.shared.f32 [%0], %1;" ::"r"(a), "f"(x) : "memory"); }
__device__ __forceinline__ uint32_t lds32(uint32_t a) { uint32_t v; asm volatile("ld.shared.u32 %0, [%1];" : "=r"(v) : "r"(a) : "memory"); return v; }
__device__ __forceinline__ uint32_t lds16(uint32_t a) { uint16_t v; asm volatile("ld.shared.u16 %0, [%1];" : "=h"(v) : "r"(a) : "memory"); return v; }
__device__ __forceinline__ float ldsf(uint32_t a) { float v; asm volatile("ld.shared.f32 %0, [%1];" : "=f"(v) : "r"(a) : "memory"); return v; }
__device__ __forceinline__ float2 ldsf2(uint32_t a) { float2 v; asm volatile("ld.shared.v2.f32 {%0, %1}, [%2];" : "=f"(v.x), "=f"(v.y) : "r"(a) : "memory"); return v; }
__device__ __forceinline__ float4 ldsf4(uint32_t a) { float4 v; asm volatile("ld.shared.v4.f32 {%0, %1, %2, %3}, [%4];" : "=f"(v.x), "=f"(v.y), "=f"(v.z), "=f"(v.w) : "r"(a) : "memory"); return v; }
__device__ __forceinline__ void stsm4(uint32_t a, uint32_t r0, uint32_t r1, uint32_t r2, uint32_t r3) { asm volatile("stmatrix.sync.aligned.m8n8.x4.shared.b16 [%0], {%1, %2, %3, %4};" ::"r"(a), "r"(r0), "r"(r1), "r"(r2), "r"(r3) : "memory"); }
__device__ __forceinline__ void stsm4t(uint32_t a, uint32_t r0, uint32_t r1, uint32_t r2, uint32_t r3) { asm volatile("stmatrix.sync.aligned.m8n8.x4.trans.shared.b16 [%0], {%1, %2, %3, %4};" ::"r"(a), "r"(r0), "r"(r1), "r"(r2), "r"(r3) : "memory"); }
__device__ __forceinline__ void ldsm4(uint32_t a, uint32_t* r) { asm volatile("ldmatrix.sync.aligned.m8n8.x4.shared.b16 {%0, %1, %2, %3}, [%4];" : "=r"(r[0]), "=r"(r[1]), "=r"(r[2]), "=r"(r[3]) : "r"(a) : "memory"); }
__device__ __forceinline__ void ldsm4t(uint32_t a, uint32_t* r) { asm volatile("ldmatrix.sync.aligned.m8n8.x4.trans.shared.b16 {%0, %1, %2, %3}, [%4];" : "=r"(r[0]), "=r"(r[1]), "=r"(r[2]), "=r"(r[3]) : "r"(a) : "memory"); }

__device__ __forceinline__ float swiglu(float g, float u) {
  const float hg = 0.5f * g, q = hg * u;
  float th;
  asm("tanh.approx.f32 %0, %1;" : "=f"(th) : "f"(hg));
  return fmaf(q, th, q);
}

struct cf { float r, i; };
__device__ __forceinline__ cf cmul(cf a, cf b) { return {a.r * b.r - a.i * b.i, a.r * b.i + a.i * b.r}; }
__device__ __forceinline__ cf csq(cf a) { return {a.r * a.r - a.i * a.i, (a.r + a.r) * a.i}; }
__device__ __forceinline__ cf cpow_seed(float a2, float beta, float p) {
  float e;
  asm("ex2.approx.ftz.f32 %0, %1;" : "=f"(e) : "f"(a2 * p));
  const float th = beta * p;
  return {e * __cosf(th), e * __sinf(th)};
}
__device__ __forceinline__ void hcmul(uint32_t r, uint32_t i, uint32_t w, uint32_t& ro, uint32_t& io) {
  const __half2 hr = *reinterpret_cast<__half2*>(&r), hi = *reinterpret_cast<__half2*>(&i), hw = *reinterpret_cast<__half2*>(&w);
  const __half2 hwr = __low2half2(hw), hwi = __high2half2(hw);
  __half2 a = __hfma2(hr, hwr, __hneg2(__hmul2(hi, hwi)));
  __half2 b = __hfma2(hr, hwi, __hmul2(hi, hwr));
  ro = *reinterpret_cast<uint32_t*>(&a);
  io = *reinterpret_cast<uint32_t*>(&b);
}

struct Modes {
  uint32_t la, ai, cr, ci;
  uint32_t e;
  float dt;
};
__device__ __forceinline__ Modes load_modes(uint32_t park, int lc, int odd_cta, int mu) {
  Modes m;
  const uint32_t a = park + 256 * lc + 4 * mu, b = park + 4224 + 8 * odd_cta + 2 * lc;
  m.la = lds32(a); m.ai = lds32(a + 1024); m.cr = lds32(a + 2048); m.ci = lds32(a + 3072);
  const uint32_t o0 = lds32((a ^ 128) + 2048), o1 = lds32((a ^ 128) + 3072), ld = lds16(b), dsk = lds16(b + 16);
  const uint32_t m2 = __vmaxu2(__vmaxu2(m.cr & 0x7fff7fffu, m.ci & 0x7fff7fffu), __vmaxu2(o0 & 0x7fff7fffu, o1 & 0x7fff7fffu));
  m.e = min(max(__reduce_max_sync(0xffffffffu, max(m2 & 0xffffu, m2 >> 16)) >> 7, 1u), 253u) << 23 | dsk;
  m.dt = bf_round(expf(bf_lo(ld)));
  return m;
}
struct Powers { uint32_t ar[2], ai[2], w[4], zr[4], zi[4], v[3], tr[3], ti[3]; float a2, beta; };
__device__ __forceinline__ void powers_a(const Modes& m, Powers& g) {
  g.a2 = -bf_round(expf(bf_lo(m.la))) * m.dt * 1.4426950408889634f;
  g.beta = bf_lo(m.ai) * m.dt;
  const cf w8 = cpow_seed(g.a2, -g.beta, 8.f), w16 = csq(w8), w32 = csq(w16), w64 = csq(w32), w128 = csq(w64), w192 = cmul(w64, w128);
  const float psd = __uint_as_float((254u << 23) - (m.e & 0xffff0000u));
  const cf a0 = {bf_lo(m.cr) * psd, -bf_lo(m.ci) * psd};
  const cf a1 = cmul(a0, w8), a2 = cmul(a0, w16), a3 = cmul(a1, w16);
  g.ar[0] = pack_f16(a0.r, a1.r); g.ar[1] = pack_f16(a2.r, a3.r);
  g.ai[0] = pack_f16(a0.i, a1.i); g.ai[1] = pack_f16(a2.i, a3.i);
  g.w[0] = pack_f16(w32.r, w32.i); g.w[1] = pack_f16(w64.r, w64.i); g.w[2] = pack_f16(w128.r, w128.i); g.w[3] = pack_f16(w192.r, w192.i);
}
__device__ __forceinline__ void powers_b(Powers& g) {
  const cf z1 = cpow_seed(g.a2, g.beta, 1.f), z2 = csq(z1), z3 = cmul(z2, z1), z4 = csq(z2), z5 = cmul(z4, z1), z6 = csq(z3), z7 = cmul(z4, z3);
  g.zr[0] = pack_f16(1.f, z4.r); g.zr[1] = pack_f16(z2.r, z6.r); g.zr[2] = pack_f16(z1.r, z5.r); g.zr[3] = pack_f16(z3.r, z7.r);
  g.zi[0] = pack_f16(0.f, z4.i); g.zi[1] = pack_f16(z2.i, z6.i); g.zi[2] = pack_f16(z1.i, z5.i); g.zi[3] = pack_f16(z3.i, z7.i);
  const cf v1 = cpow_seed(g.a2, g.beta, 256.f), v2 = csq(v1), v3 = cmul(v2, v1), v4 = csq(v2), v5 = cmul(v4, v1), v6 = csq(v3), v7 = cmul(v4, v3), v8 = csq(v4);
  g.v[0] = pack_f16(v1.r, v1.i); g.v[1] = pack_f16(v2.r, v2.i); g.v[2] = pack_f16(v3.r, v3.i);
  g.tr[0] = pack_f16(v4.r, v5.r); g.tr[1] = pack_f16(v6.r, v7.r); g.tr[2] = pack_f16(v8.r, 0.f);
  g.ti[0] = pack_f16(v4.i, v5.i); g.ti[1] = pack_f16(v6.i, v7.i); g.ti[2] = pack_f16(v8.i, 0.f);
}
__device__ __forceinline__ void kgen_operands(const Powers& g, uint32_t buf, int chi, int mu) {
  const uint32_t sa = buf + chi * 8192 + mu * 16, sbb = buf + 16384 + chi * 6144 + mu * 16;
  uint32_t R[4] = {g.ar[0], g.ar[1]}, I[4] = {g.ai[0], g.ai[1]}, r[4], i[4];
  sts128(sbb, g.zr[0], g.zr[1], g.zr[2], g.zr[3]); sts128(sbb + 1024, g.zi[0], g.zi[1], g.zi[2], g.zi[3]);
  hcmul(g.zr[0], g.zi[0], g.v[0], r[0], i[0]); hcmul(g.zr[1], g.zi[1], g.v[0], r[1], i[1]);
  hcmul(g.zr[0], g.zi[0], g.v[1], r[2], i[2]); hcmul(g.zr[0], g.zi[0], g.v[2], r[3], i[3]);
  sts128(sbb + 4096, g.tr[0], g.tr[1], g.tr[2], 0); sts128(sbb + 5120, g.ti[0], g.ti[1], g.ti[2], 0);
  hcmul(R[0], I[0], g.w[0], R[2], I[2]); hcmul(R[1], I[1], g.w[0], R[3], I[3]);
  sts128(sbb + 2048, r[0], r[1], r[2], r[3]); sts128(sbb + 3072, i[0], i[1], i[2], i[3]);
#pragma unroll
  for (int q = 1; q < 4; q++) {
#pragma unroll
    for (int k = 0; k < 4; k++) hcmul(R[k], I[k], g.w[q], r[k], i[k]);
    if (q == 1) { sts128(sa, R[0], R[1], R[2], R[3]); sts128(sa + 1024, I[0], I[1], I[2], I[3]); }
    sts128(sa + 2048 * q, r[0], r[1], r[2], r[3]); sts128(sa + 2048 * q + 1024, i[0], i[1], i[2], i[3]);
  }
  fence_async_smem();
}
template <int NK> __device__ __forceinline__ void kgen_mma(float (&dk)[24], uint32_t buf, int scale) {
  const uint32_t da = (buf >> 4) | (64u << 16), db = da + 1024;
  wg_fence();
#pragma unroll
  for (int k = 0; k < NK; k++) mma_kgen(dk, da + 8 * k, db + 8 * k, scale | k);
  wg_commit();
}
__device__ __forceinline__ void kgen_dump(const float (&dk)[24], float pks, float skip, uint32_t kc, uint32_t s0, int w4, int lane) {
  const int chi = w4 >> 1, g = lane >> 2, t = lane & 3, mu = 32 * (w4 & 1) + lane;
  const int i0 = 16 * (w4 & 1) + g;
  float v[12];
#pragma unroll
  for (int k = 0; k < 12; k++) v[k] = (chi ? dk[12 + k] : dk[k]) * pks;
  if (mu == 0) v[0] += skip;
  const uint32_t b = kc + 4 * (t < 2 ? 4 + 4 * i0 + t : 4 + 64 * t + 2 * i0);
  const uint32_t be = t < 2 ? 8 : 4;
  stsf(b, v[4]); stsf(b + be, v[5]); stsf(b + 16 * be, v[6]); stsf(b + 17 * be, v[7]);
  const uint32_t c = kc + 4 * (260 + 64 * t + i0);
  if (t < 2) { stsf(c, v[8]); stsf(c + 128, v[9]); stsf(c + 32, v[10]); stsf(c + 160, v[11]); }
  else if (t == 2 && i0 == 0) stsf(c, v[8]);
  else if (mu == 63) stsf(kc + 12, v[3]);
  const uint32_t a = s0 + 16 * i0 + 2 * ((t & 1) * 2 + (t >> 1));
  const uint32_t e0 = pack_bf16(v[0], v[1]), e1 = pack_bf16(v[2], v[3]);
  sts16(a, e0); sts16(a + 8, e0 >> 16); sts16(a + 128, e1); sts16(a + 136, e1 >> 16);
  sts16(a + KT_COPY + 2, e0); sts16(a + KT_COPY + 10, e0 >> 16); sts16(a + KT_COPY + 130, e1);
  if (mu != 63) sts16(a + KT_COPY + 138, e1 >> 16);
  if (mu < 14) sts128(s0 - 112 + 16 * mu + (mu < 7 ? 0 : KT_COPY - 112), 0, 0, 0, 0);
  else if (mu == 14) sts16(s0 + KT_COPY, 0);
}
template <bool LEAN> __device__ __forceinline__ void kgen_expand(uint32_t kc, uint32_t s0, int w4, int lane) {
  const int mu = 32 * (w4 & 1) + lane;
  const bool odd = w4 & 1;
  const float4 a = ldsf4(kc + 16 + 16 * lane);
  float ax = ldsf(odd ? kc + 12 : kc + 32 + 16 * lane);
  float2 q;
  float q2, r[4];
  auto load_q = [&]() { q = ldsf2(kc + 528 + 8 * mu); q2 = ldsf(kc + 536 + 8 * mu); };
  auto load_r = [&](int k) { r[2 * k] = ldsf(kc + 1040 + 256 * k + 4 * mu); r[2 * k + 1] = ldsf(kc + 1044 + 256 * k + 4 * mu); };
  if (!LEAN) { load_q(); load_r(0); load_r(1); }
  {
    const uint32_t c22 = pack_bf16(a.z, a.z);
    if (!odd) sts128(s0 + 512 + 16 * lane, pack_bf16(a.x, a.x), pack_bf16(a.y, a.z), c22, pack_bf16(a.w, ax));
    else sts128(s0 + KT_COPY + 512 + 16 * lane, pack_bf16(lane ? a.x : ax, a.x), pack_bf16(a.x, a.y), c22, pack_bf16(a.z, a.w));
  }
  if (LEAN) { load_q(); load_r(0); }
  const uint32_t sm0 = s0 + 16 * mu, sm1 = sm0 + KT_COPY;
  {
    const uint32_t c00 = pack_bf16(q.x, q.x), c11 = pack_bf16(q.y, q.y);
    sts128(sm0 + 1024, c00, pack_bf16(q.x, q.y), c11, pack_bf16(q2, q2));
    sts128(sm1 + 1024, c00, c00, c11, pack_bf16(q.y, q2));
  }
  if (LEAN) load_r(1);
#pragma unroll
  for (int k = 0; k < 2; k++) {
    const float pa = r[2 * k], pb = r[2 * k + 1], px = (lane & 1) ? pb : pa;
    const uint32_t caa = pack_bf16(pa, pa), cbb = pack_bf16(pb, pb);
    sts128(sm0 + 2048 + 1024 * k, caa, caa, pack_bf16(px, pb), cbb);
    sts128(sm1 + 2048 + 1024 * k, caa, caa, pack_bf16(pa, px), cbb);
  }
  fence_async_smem();
}

__host__ __device__ constexpr int conv_step(int i) {
  return CONV_ORDER == 0 ? i >> 1
       : CONV_ORDER == 1 ? ((i & 2) ? 15 - (i >> 2) : i >> 2)
       : CONV_ORDER == 2 ? ((i & 1) ? 15 - (i >> 2) : i >> 2)
       : CONV_ORDER == 3 ? ((i & 3) == 0 ? i >> 3 : (i & 3) == 1 ? 8 + (i >> 3) : (i & 3) == 2 ? 7 - (i >> 3) : 15 - (i >> 3))
                         : ((i & 1) ? 8 + (i >> 2) : i >> 2);
}
__host__ __device__ constexpr int conv_par(int i) { return CONV_ORDER <= 1 ? i & 1 : CONV_ORDER == 3 ? (i >> 2) & 1 : (i >> 1) & 1; }
template <int I> struct ConvSeq {
  static __device__ __forceinline__ void run(float (&d)[64], uint32_t a, uint32_t b) {
    constexpr int J = conv_step(I), S = conv_par(I);
    mma_conv<128 - 8 * J>(d, a + S * (KT_COPY / 16) + 16 * J, b + S * (UT_PAR / 16) + 8 * J, I != 0);
    ConvSeq<I + 1>::run(d, a, b);
  }
};
template <> struct ConvSeq<32> { static __device__ __forceinline__ void run(float (&)[64], uint32_t, uint32_t) {} };

struct Params {
  const __nv_bfloat16 *x, *w_gate, *w_up, *log_a, *a_im, *c_re, *c_im, *log_dt, *d_skip, *gate_w, *w_down;
};

__device__ __forceinline__ void extra_cta(const Params& p, const CUtensorMap* tm_x) {
  constexpr uint32_t sd = 1024, WGRP = 8208, OFF_X = 74752, B_F = OFF_BAR, B_W = OFF_BAR + 128;
  const uint32_t sb = sd + ((blockIdx.x & 1) << 24);
  const int warp = __shfl_sync(0xffffffffu, threadIdx.x >> 5, 0), lane = threadIdx.x & 31, wg = warp >> 2;
  const int row0 = 512 * (blockIdx.x - 128);
  auto x_load = [&](int ks) {
    const uint32_t bar = sb + B_F + 32 * wg + 8 * (ks & 3);
    mbar_expect(bar, 8192);
    tma2d(sb + OFF_X + 32768 * wg + 8192 * (ks & 3), tm_x, bar, 32 * ks, row0 + 128 * wg);
  };
  const int k = threadIdx.x, ng = k & 7;
  const uint8_t* wsrc = (const uint8_t*)(ng < 4 ? p.w_gate : p.w_up) + (k >> 3) * (kF * 2) + 2688 + 16 * (ng & 3);
  auto w_load = [&](int q) {
    if (q < 8) cp_async16(sb + ng * WGRP + (64 * q + (k >> 3)) * 16, wsrc + q * (64 * kF * 2));
    asm volatile("cp.async.commit_group;" ::: "memory");
  };
  const uint32_t gw = __ldg((const uint16_t*)p.gate_w + k);
  w_load(0);
  w_load(1);
  if (!(k & 127)) {
#pragma unroll
    for (int i = 0; i < 4; i++) mbar_init(sb + B_F + 32 * wg + 8 * i, 1);
    mbar_init(sb + B_W + 16 * wg, 16); mbar_init(sb + B_W + 16 * wg + 8, 16);
    fence_async_smem();
#pragma unroll 1
    for (int ks = 0; ks < 3; ks++) x_load(ks);
  }
  sts128(sb + 8 * WGRP + 16 * k, gw, 0, 0, 0);
  asm volatile("cp.async.wait_group 1;" ::: "memory");
  fence_async_smem();
  XT(16);
  __syncthreads();
  XT(17);
  w_load(2);
  float d0[36], d1[36];
#pragma unroll 1
  for (int ks = 0; ks < 16; ks++) {
    if (!(ks & 1) && ks) mbar_wait(sb + B_W + 4 * ks, 0);
    mbar_wait(sb + B_F + 32 * wg + 8 * (ks & 3), (ks >> 2) & 1);
    const uint32_t da = ((sd + OFF_X + 32768 * wg + 8192 * (ks & 3)) >> 4) | (1u << 16), db = ((sd >> 4) + 32 * ks) | (8u << 16);
    wg_fence();
    mma_x(d0, da, db, ks);
    mma_x(d1, da + 256, db, ks);
    mma_x(d0, da + 2, db + 16, 1);
    mma_x(d1, da + 258, db + 16, 1);
    wg_commit();
    if (!(ks & 1) && ks < 14) {
      asm volatile("cp.async.wait_group 1;" ::: "memory");
      fence_async_smem();
      __syncwarp();
      if (lane == 0) mbar_arrive(sb + B_W + 4 * ks + 8);
      w_load(ks / 2 + 3);
    }
    wg_wait<1>();
    nb_sync(1 + wg, 128);
    if (!(k & 127) && ks < 13) x_load(ks + 3);
    __syncwarp();
  }
  XT(15);
  wg_wait<0>();
  pin(d0); pin(d1);
  uint8_t* hp = g_h + ((size_t)(row0 / 64 + 2 * (warp >> 2)) * 88 + 84) * 2048 + (warp & 3) * 256 + lane * 4;
#pragma unroll
  for (int e = 0; e < 8; e++) {
    *(uint32_t*)(hp + (e >> 1) * 1024 + (e & 1) * 128) = pack_bf16(swiglu(d0[2 * e], d0[16 + 2 * e]), swiglu(d0[2 * e + 1], d0[17 + 2 * e]));
    *(uint32_t*)(hp + 88 * 2048 + (e >> 1) * 1024 + (e & 1) * 128) = pack_bf16(swiglu(d1[2 * e], d1[16 + 2 * e]), swiglu(d1[2 * e + 1], d1[17 + 2 * e]));
  }
  {
    const float l0 = __shfl_sync(0xffffffffu, d0[32], lane & 28), l1 = __shfl_sync(0xffffffffu, d0[34], lane & 28);
    const float l2 = __shfl_sync(0xffffffffu, d1[32], lane & 28), l3 = __shfl_sync(0xffffffffu, d1[34], lane & 28);
    const float lg = (lane & 2) ? ((lane & 1) ? l3 : l2) : ((lane & 1) ? l1 : l0);
    const float gt = bf_round(1.f / (1.f + expf(-bf_round(lg))));
    g_gate[row0 + 128 * (warp >> 2) + 32 * (lane & 2) + 16 * (warp & 3) + 8 * (lane & 1) + (lane >> 2)] = pack_bf16(gt, 1.f - gt);
  }
  XT(18);
  __syncthreads();
  if (warp == 0) {
    fence_async_all();
    XT(19);
    if (lane < 8) asm volatile("red.relaxed.gpu.global.add.u32 [%0], 8;" ::"l"(g_flags + (FL_H + row0 / 64 + lane) * FLAG_STRIDE) : "memory");
  }
}

}

__global__ void __cluster_dims__(2, 1, 1) __launch_bounds__(512, 1)
gated_mix_kernel(const Params p, const __grid_constant__ CUtensorMap tm_x, const __grid_constant__ CUtensorMap tm_wg,
                 const __grid_constant__ CUtensorMap tm_wg3, const __grid_constant__ CUtensorMap tm_wu,
                 const __grid_constant__ CUtensorMap tm_wu3, const __grid_constant__ CUtensorMap tm_wd,
                 const __grid_constant__ CUtensorMap tm_out, const __grid_constant__ CUtensorMap tm_u,
                 const __grid_constant__ CUtensorMap tm_xp, const __grid_constant__ CUtensorMap tm_ul) {
  extern __shared__ uint8_t smem_raw[];
  constexpr uint32_t sd = 1024;
  if (blockIdx.x >= 128) { extra_cta(p, &tm_x); return; }
  const int rank = blockIdx.x & 1, cl = blockIdx.x >> 1;
  const uint32_t sb = sd + ((uint32_t)rank << 24);
  if (threadIdx.x == 416) {
    asm volatile("prefetch.tensormap [%0];" ::"l"(&tm_wg + 2 * rank) : "memory");
    asm volatile("prefetch.tensormap [%0];" ::"l"(&tm_wg3 + 2 * rank) : "memory");
    asm volatile("prefetch.tensormap [%0];" ::"l"(&tm_x) : "memory");
  }
  if (threadIdx.x < 64 * PF_MULT) {
    const int k = threadIdx.x & 63, share = (blockIdx.x * PF_MULT + ((threadIdx.x >> 6) & 3)) & 127;
    const uint8_t* a = k < 16 ? (const uint8_t*)p.x + (16 * share + k) * 1024
                              : (const uint8_t*)(k < 32 ? p.w_gate : p.w_up) + (11 * share + (k & 15)) * 128;
    if (k < 27 || (k >= 32 && k < 43)) asm volatile("prefetch.global.L2 [%0];" ::"l"(a) : "memory");
  }
  const int warp = __shfl_sync(0xffffffffu, threadIdx.x >> 5, 0);
  const int lane = threadIdx.x & 31;
  const int wg = warp >> 2, w4 = warp & 3;
  const int row7 = ((cl - 36) * 37) >> 8;
  const int ia = 8 + 2 * cl, ib = 16 * ((cl - 4) & 7) + 2 * ((cl - 4) >> 3), ic = 16 * cl - 552 - 110 * row7;
  const int cta = rank + selp(ia, selp(ib, ic, cl < 36), cl < 4);
  const int mb = 2 * (cta >> 4) + rank;
  const int nb = (cta >> 1) & 7;
  const int m2 = cta >> 3;
  const int tb = 2 * m2 + rank;
  const int cq = (cta >> 1) & 3;

  auto g1_load = [&](int ks, uint32_t slot) {
    const uint32_t bar = sb + B_FULL1 + 8 * slot, dst = sb + slot * SLOT1;
    mbar_expect(bar, 8192 + 2 * (8192 + 2560));
    tma3d_pair(dst + 8192 + 12288 * rank, &tm_wg + 2 * rank, bar, 64 * nb, 32 * ks, 0);
    tma2d_pair(dst + 16384 + 12288 * rank, &tm_wg3 + 2 * rank, bar, 1024 + 40 * nb, 32 * ks);
    tma2d(dst, &tm_x, bar, 32 * ks, 128 * mb);
  };

  if (wg == 2) {
    const int tau = threadIdx.x & 127, o = 1024 * cta + 16 * (tau & 63);
    cp_async16(sb + OFF_PARK + 16 * tau, (const uint8_t*)(w4 < 2 ? p.log_a : p.a_im) + o);
    cp_async16(sb + OFF_PARK + 2048 + 16 * tau, (const uint8_t*)(w4 < 2 ? p.c_re : p.c_im) + o);
    if (!(tau & 63)) cp_async16(sb + OFF_PARK + 4224 + 8 * w4, (const uint8_t*)(w4 ? p.d_skip : p.log_dt) + 16 * (cta >> 1));
    TL(8);
  }
  if ((threadIdx.x & ~96) == 128) {
    if (threadIdx.x == 128) init_barriers<0, 14>(sb + OFF_BAR);
    else if (threadIdx.x == 160) init_barriers<14, 28>(sb + OFF_BAR);
    else if (threadIdx.x == 192) init_barriers<28, 41>(sb + OFF_BAR);
    else init_barriers<41, 56>(sb + OFF_BAR);
    asm volatile("fence.mbarrier_init.release.cluster;" ::: "memory");
    fence_async_smem();
  }
  __syncwarp();
  asm volatile("barrier.cluster.arrive.relaxed.aligned;" ::: "memory");
  if (warp == 12) {
    TL(1);
    cluster_wait();
    if (elect()) {
      TLW(2);
#pragma unroll 1
      for (int ks = 0; ks < HEAD_STAGES; ks++) g1_load(ks, ks);
      TLW(3);
    }
    __syncwarp();
  }

  if (wg == 3) {
    asm volatile("setmaxnreg.dec.sync.aligned.u32 24;");
    if (w4) cluster_wait();
    auto h_publish = [&](int w) {
      uint32_t* f = g_flags + (FL_H + 2 * mb + w) * FLAG_STRIDE;
      asm volatile("" : "+l"(f));
      nb_sync(NB_H0 + w, 160);
      TLQ(t1);
      if (elect()) {
        asm volatile("red.release.gpu.global.add.u32 [%0], 3;" ::"l"(f) : "memory");
      }
      __syncwarp();
      TLQ(t2);
      TLS(58 + w, t1);
      TLS(60 + w, t2);
    };
    const uint8_t* hsrc = g_h + ((size_t)2 * m2 * 88 + 43 * rank) * 2048;
    if (w4 >= 2) {
      const int ii = lane & 7;
      const uint32_t src = sb + OFF_A + (64 * (w4 & 1) + 7 - ii) * 128 + 16 * ((lane >> 3) ^ (7 - ii));
      const uint32_t dst = sb + OFF_UT + lane * 128 + 16 * ((4 * (1 - (w4 & 1))) ^ ii);
      mbar_wait(sb + B_XTFULL, 0);
#pragma unroll 1
      for (int r = 0; r < 8; r++) {
        uint32_t v[8];
        ldsm4(src + r * 1024, v);
        ldsm4((src + r * 1024) ^ 64, v + 4);
        const uint32_t o = (dst + (r & 1) * 8192) ^ (8 * (r & 6));
        stsm4t(o, v[0], v[1], v[2], v[3]);
        stsm4t(o + 4096, v[4], v[5], v[6], v[7]);
      }
      fence_async_smem();
      nb_arrive(NB_UT, 96);
      TLW(20);
      nb_sync(NB_KC0, 192);
#pragma unroll 1
      for (int half = 0; half < 2; half++) {
        kgen_expand<true>(sb + OFF_PARK + (w4 & 1) * KC_CH, sb + OFF_A + (w4 & 1) * KT_CH + 112, half, lane);
        __syncwarp();
        if (lane == 0) mbar_arrive(sb + B_TAB);
      }
      TLW(35);
    }
    if (w4 == 0) {
      if ((uint32_t)__cvta_generic_to_shared(smem_raw) != sb) __trap();
      uint32_t slot = HEAD_STAGES, ph = 1;
#pragma unroll 1
      for (int ks = HEAD_STAGES; ks < 16; ks++) {
        mbar_wait(sb + B_EMPTY1 + 8 * slot, ph);
        if (elect()) g1_load(ks, slot);
        if (ks == HEAD_STAGES) TL(47);
        __syncwarp();
        if (ks == 4) TL(49);
        if (++slot == 5) { slot = 0; ph ^= 1; }
      }
      if (elect()) mbar_expect(sb + B_WF, 5 * 16384);
#pragma unroll 1
      for (int q = 0; q < 11; q++) {
        const int st = q < 4 ? q + 1 : q == 4 ? 0 : q;
        slot = st < 6 ? st : st - 6;
        mbar_wait(sb + (q < 4 ? B_EMPTY1 + 8 + 8 * (q >> 1) : q == 4 ? B_G1DONE : q == 5 ? B_PEMPTY + 16 : B_EMPTYW + 8 * slot), 0);
        if (elect()) {
          const uint32_t bar = sb + (st < 5 ? B_WF : st == 5 ? B_W5 : B_FULL3 + 8 * slot);
          if (st >= 5) mbar_expect(bar, 16384);
          tma3d(sb + OFF_W2 + 16384 * slot, &tm_wd, bar, 0, 688 * rank + 64 * st, 2 * cq);
        }
        __syncwarp();
      }
    } else if (w4 == 1) {
      uint32_t target;
      asm volatile("ld.relaxed.gpu.global.u32 %0, [%1];" : "=r"(target) : "l"(g_flags + (FL_U + nb) * FLAG_STRIDE) : "memory");
      target = (target & ~31u) + 32;
      if (elect()) {
        sts32(sb + OFF_EPOCH, target);
        mbar_expect(sb + B_XTFULL, 16384);
        tma4d(sb + OFF_A, &tm_xp, sb + B_XTFULL, 64 * nb, 0, 0, 2 * mb);
#pragma unroll
        for (int i = 0; i < 5; i++) if (i != 3) asm volatile("prefetch.tensormap [%0];" ::"l"(&tm_wd + i) : "memory");
      }
      __syncwarp();
      nb_sync(NB_UT, 96);
      if (elect()) {
        mbar_arrive(sb + B_XTREAD);
        tma3d_store(&tm_u, sb + OFF_UT, 32 * (30 - 2 * mb), 64 * nb, 0);
        asm volatile("cp.async.bulk.commit_group;" ::: "memory");
        asm volatile("cp.async.bulk.wait_group 0;" ::: "memory");
        TLW(55);
      }
      __syncwarp();
      if (elect()) {
        flag_signal(FL_U + nb, 2);
        TLW(56);
        asm volatile("cp.async.bulk.prefetch.L2.global [%0], %1;" ::"l"((const uint8_t*)p.w_down + (size_t)cta * 11008), "r"(11008) : "memory");
        mbar_expect(sb + B_UFULL, 4 * UT_CH);
        flag_wait(FL_U + (cta >> 4), target);
        tma4d(sb + OFF_UT, &tm_ul, sb + B_UFULL, 0, 0, 0, 4 * cta);
        TLW(57);
        mbar_expect(sb + B_RECV, 16384);
      }
      __syncwarp();
      mbar_wait(sb + B_G1DONE, 0);
      if (elect()) {
#pragma unroll 1
        for (int s = 0; s < 6; s++) mbar_expect(sb + B_HE + 8 * s, 8192);
        flag_wait(FL_H + 2 * m2, target);
        TLW(40);
#pragma unroll
        for (int s = 0; s < 6; s++) bulk_load(sb + OFF_HE + 8192 * s, hsrc + s * 8192, 8192, sb + B_HE + 8 * s);
        if (rank == 0) flag_wait(FL_H + 2 * m2 + 1, target);
#pragma unroll 1
        for (int s = 0; s < 5; s++) {
          const uint32_t bytes = s == 4 ? 6144 : 8192;
          mbar_expect(sb + B_FULL3 + 8 * s, bytes);
          mbar_wait(sb + B_EMPTYH + 8 * s, 0);
          bulk_load(sb + OFF_HE + 8192 * s, hsrc + (rank ^ 1) * (88 * 2048) + 49152 + s * 8192, bytes, sb + B_FULL3 + 8 * s);
        }
      }
      __syncwarp();
    } else if (w4 == 2) {
      h_publish(0);
      mbar_wait(sb + B_PEMPTY + 24, 0);
      if (elect()) {
        mbar_expect(sb + B_YFULL, 16384);
        flag_wait(FL_Y + cq, lds32(sb + OFF_EPOCH));
        bulk_load(sb + OFF_P, g_y + ((size_t)tb * 512 + 128 * cq) * 128, 16384, sb + B_YFULL);
        TLW(41);
      }
      __syncwarp();
    } else {
      if (elect()) {
#pragma unroll 1
        for (int s = 0; s < 6; s++) mbar_expect(sb + B_HL + 8 * s, 8192);
        mbar_expect(sb + B_KH, 38912 + 256);
      }
      __syncwarp();
      const uint32_t target = lds32(sb + OFF_EPOCH);
      h_publish(1);
      if (elect()) {
        flag_wait(FL_H + 2 * m2 + 1, target);
        TLW(39);
        mbar_wait(sb + B_C12, 0);
#pragma unroll
        for (int s = 0; s < 6; s++) bulk_load(sb + (s < 5 ? OFF_A + 8192 * s : OFF_HL5), hsrc + 88 * 2048 + s * 8192, 8192, sb + B_HL + 8 * s);
        bulk_load(sb + OFF_GATE, g_gate + 64 * tb, 256, sb + B_KH);
        mbar_wait(sb + B_EMPTYW + 32, 0);
        bulk_load(sb + OFF_A, hsrc + rank * (88 * 2048) + 49152, 38912, sb + B_KH);
      }
      __syncwarp();
      mbar_wait(sb + B_DONE, 0);
      return;
    }
    if (lane == 0) mbar_arrive(sb + B_DONE);
  } else if (wg == 2) {
    asm volatile("setmaxnreg.dec.sync.aligned.u32 88;");
    const int tau = threadIdx.x & 127, chi = w4 >> 1, mu = tau & 63;

    const uint32_t kc = sb + OFF_PARK + chi * KC_CH;
    TL(9);
    cluster_wait();
    asm volatile("cp.async.wait_all;" ::: "memory");
    nb_sync(NB_AUX, 128);
    TL(51);
    Modes m = load_modes(sb + OFF_PARK, conv_ch(chi), cta & 1, mu);
    Powers pw;
    powers_a(m, pw);
    powers_b(pw);
    TL(50);
    float dk[24];
#pragma unroll 1
    for (int it = 0; it < 4; it++) {
      kgen_operands(pw, sb + OFF_KS, chi, mu);
      nb_sync(NB_AUX, 128);
      TL(21 + 3 * it);
      int tid_local = threadIdx.x;
      asm volatile("" : "+r"(tid_local), "+r"(m.e));
      const int lane = tid_local & 31, mu = tid_local & 63;
      kgen_mma<KB1>(dk, sd + OFF_KS, it & 1);
      float pks = 2.f * m.dt * bf_hi(m.e), skip = bf_lo(m.e);
      asm volatile("" : "+f"(pks), "+f"(skip));
      if (it == 1) {
        m = load_modes(sb + OFF_PARK, conv_ch(2 + chi), cta & 1, mu);
      } else {
        m.la >>= 16; m.ai >>= 16; m.cr >>= 16; m.ci >>= 16;
      }
      if (it < 3) powers_a(m, pw);
      if (KB1 < 8) kgen_mma<8 - KB1>(dk, sd + OFF_KS + 128 * KB1, 1);
      if (it < 3) powers_b(pw);
      wg_wait<0>();
      pin(dk);
      nb_sync(NB_AUX, 128);
      TL(22 + 3 * it);
      if (it & 1) mbar_wait(sb + (it == 1 ? B_XTREAD : B_TAB), 0);
      if (it & 1) kgen_dump(dk, pks, skip, kc, sb + (it == 1 ? OFF_A : OFF_KT23) + chi * KT_CH + 112, w4, lane);
      if (it == 1) { fence_async_smem(); nb_arrive(NB_KC0, 192); }
    }
    nb_sync(NB_AUX, 128);
    kgen_expand<false>(kc, sb + OFF_KT23 + chi * KT_CH + 112, w4, lane);
    __syncwarp();
    if (lane == 0) mbar_arrive(sb + B_TAB + 8);
    TLK(32);

    {
      const int half = lane >> 4, wd = 16 * (w4 & 1) + (lane & 15), row0 = 16 * (w4 >> 1) + half;
      uint32_t pa[4];
#pragma unroll
      for (int r = 0; r < 4; r++) {
        const int sw = (wd - r) & 31, row = row0 - (wd < r);
        pa[r] = sb + OFF_P + r * 4096 + row * 128 + 16 * ((sw >> 2) ^ r ^ (4 * (row & 1))) + 4 * (sw & 3);
      }
#pragma unroll 1
      for (int c = 0; c < 4; c++) {
        const int ch = 4 * cta + conv_ch(c);
        uint8_t* yo = g_y + ((size_t)row0 * 512 + ch) * 128 + 16 * ((wd >> 2) ^ (ch & 7)) + 4 * (wd & 3);
        nb_sync(NB_PFULL0 + (c & 1), 256);
        uint32_t o[8];
        const uint32_t pb = (c & 1) ? 0 : OFF_RECV;
#pragma unroll
        for (int k = 0; k < 8; k++) {
          uint32_t v0 = lds32(pa[0] + pb + 256 * k), v1 = lds32(pa[1] + pb + 256 * k), v2 = lds32(pa[2] + pb + 256 * k), v3 = lds32(pa[3] + pb + 256 * k);
          if (k == 0 && row0 == 0) { if (wd < 1) v1 = 0; if (wd < 2) v2 = 0; if (wd < 3) v3 = 0; }
          o[k] = badd2(badd2(v0, v1), badd2(v2, v3));
        }
#pragma unroll
        for (int k = 0; k < 8; k++) *(uint32_t*)(yo + (size_t)k * 131072) = o[k];
        __syncwarp();
        if (lane == 0) mbar_arrive(sb + B_PEMPTY + 8 * c);
        if (c >= 2) TLK(34 + c);
      }
      nb_sync(NB_AUX, 128);
      if (tau == 0) flag_signal(FL_Y + (cta >> 5), 1);
      __syncwarp();
    }
    TLK(38);
    if (lane == 0) mbar_arrive(sb + B_DONE);
  } else {
    asm volatile("setmaxnreg.inc.sync.aligned.u32 200;");
    cluster_wait();
    TLR_DECL;
    {
      float ag[84], au[84];
      const uint32_t da0 = ((sd >> 4) + wg * 256) | (1u << 16);
      constexpr uint32_t db0 = ((sd >> 4) + 512) | (256u << 16);
      const uint32_t rel = sd + B_EMPTY1 + (lane << 24);
      auto release = [&](int slot) { if (lane < 2) mbar_arrive_cluster(rel + 8 * slot); };
      auto g1_stage = [&](int slot, uint32_t ph, int scale) {
        mbar_wait(sb + B_FULL1 + 8 * slot, ph);
        const uint32_t da = da0 + slot * (SLOT1 / 16), db = db0 + slot * (SLOT1 / 16);
        wg_fence();
        mma_g1(ag, da, db, scale);
        mma_g1(au, da, db + 768, scale);
        if (G1SPLIT == 2) wg_commit();
        mma_g1(ag, da + 2, db + 128, 1);
        if (G1SPLIT == 3) wg_commit();
        mma_g1(au, da + 2, db + 768 + 128, 1);
        wg_commit();
      };
      if (wg == 0) TL(10);
#pragma unroll 1
      for (int it = 0; it < 2; it++) {
#pragma unroll
        for (int q = 0; q < 5; q++) {
          g1_stage(q, it, it | q);
          if (q == 0 && it == 0) TLK(4 + wg);
          wg_wait<2>();
          if (q || it) release((q + 4) % 5);
          wg_wait<1>();
        }
      }
#pragma unroll
      for (int q = 0; q < 6; q++) {
        if (q == SKEWQ && wg == 1) { wg_wait<0>(); release(q - 1); nb_sync(NB_SKEW, 256); }
        g1_stage(q % 5, q / 5, 1);
        if (q == 5) nb_arrive(wg ? NB_GO0 : NB_SKEW, 256);
        if (q < 5) {
          wg_wait<2>();
          if (!(q == SKEWQ && wg == 1)) release((q + 4) % 5);
          if (q < SKEWQ - 1) wg_wait<1>();
        }
      }
      wg_wait<0>();
      pin(ag); pin(au);
      if (lane == 0) mbar_arrive(sb + B_G1DONE);
      TLR(0);
      uint8_t* hp = g_h + (size_t)(2 * mb + wg) * 88 * 2048 + nb * 8192 + w4 * 256 + lane * 4;
#pragma unroll
      for (int j = 0; j < 21; j++) {
        if (j == 16) hp -= nb * 3072;
#pragma unroll
        for (int e = 0; e < 2; e++)
          *(uint32_t*)(hp + (j >> 3) * 65536 + (j & 7) * 1024 + e * 128) =
              pack_bf16(swiglu(ag[4 * j + 2 * e], au[4 * j + 2 * e]), swiglu(ag[4 * j + 2 * e + 1], au[4 * j + 2 * e + 1]));
        if (EPI_GROUP && j % EPI_GROUP == EPI_GROUP - 1) sched_fence(gridDim.x, j);
      }
      nb_arrive(NB_H0 + wg, 160);
      TLR(1);
    }
    const int mat = lane >> 3, ii = lane & 7;
    {
      const uint32_t pw = sb + (wg ? OFF_P : OFF_RECV) + (ii & 3) * 4096 + (31 - 2 * (mat >> 1) - (ii >> 2)) * 128 +
                          16 * ((2 * w4 + (mat & 1)) ^ (ii & 3) ^ (4 * (1 - (ii >> 2))));
      mbar_wait(sb + B_UFULL, 0);
#pragma unroll 1
      for (int c = wg; c < 4; c += 2) {
        mbar_wait(sb + B_TAB + 8 * (c >> 1), 0);
        const uint32_t da = ((sd + (c < 2 ? OFF_A : OFF_KT23) + wg * KT_CH) >> 4) | (8u << 16);
        const uint32_t db = ((sd + OFF_UT + conv_ch(c) * UT_CH) >> 4) | (4u << 16);
        nb_sync(NB_GO0 + wg, 256);
        float d[64];
        wg_fence();
        ConvSeq<0>::run(d, da, db);
        wg_commit();
        if (!(EHOLD && c == 3)) nb_arrive(NB_GO0 + (wg ^ 1), 256);
        mbar_wait(sb + (c < 2 ? B_G1DONE : B_PEMPTY + 8 * wg), 0);
        wg_wait<0>();
        pin(d);
        if (c < 2) TLR(2); else TLR(6);
        if ((c == 1 || c == 2) && lane == 0) mbar_arrive(sb + B_C12);
#pragma unroll
        for (int q = 0; q < 8; q++)
          stsm4t(pw - 512 * q, pack_bf16(d[8 * q], d[8 * q + 1]), pack_bf16(d[8 * q + 2], d[8 * q + 3]),
                 pack_bf16(d[8 * q + 4], d[8 * q + 5]), pack_bf16(d[8 * q + 6], d[8 * q + 7]));
        nb_arrive(NB_PFULL0 + wg, 256);
        if (EHOLD == 1 && c == 3) nb_arrive(NB_GO0, 256);
        if (c < 2) TLR(3); else TLR(7);
      }
    }
    const bool keeper = wg == rank;
    const uint32_t peer = sb ^ (1u << 24);
    float d[64];
    auto g2_stage = [&](uint32_t da, int slot, int nk, int scale) {
      const uint32_t db = ((sd + OFF_W2 + 16384 * slot) >> 4) | (512u << 16);
      wg_fence();
      mma_g2(d, da, db, scale);
      mma_g2(d, da + 128, db + 128, 1);
      mma_g2(d, da + 256, db + 256, 1);
      if (nk == 4) mma_g2(d, da + 384, db + 384, 1);
      wg_commit();
    };
    constexpr uint32_t dae = ((sd + OFF_HE) >> 4) | (64u << 16), dal = ((sd + OFF_A) >> 4) | (64u << 16);
    {
      const uint32_t da = wg ? dal : dae, da5 = wg ? ((sd + OFF_HL5) >> 4) | (64u << 16) : dae + 5 * 512;
      mbar_wait(sb + B_WF, 0);
      mbar_wait(sb + B_HE - 48 * wg, 0);
      if (EHOLD == 2) mbar_wait(sb + B_PEMPTY + 24, 0);
      else if (wg == 0) nb_sync(NB_GO0, 256);
      TLR(8);
#pragma unroll
      for (int st = 0; st < 6; st++) {
        g2_stage(st < 5 ? da + 512 * st : da5, st, 4, st);
        if (st < 5) mbar_wait(sb + B_HE - 48 * wg + 8 * (st + 1), 0);
        if (st == 4) mbar_wait(sb + B_W5, 0);
        if (st > 0) {
          wg_wait<1>();
          if (lane == 0) { if (!wg) mbar_arrive(sb + B_EMPTYH + 8 * (st - 1)); mbar_arrive(sb + B_EMPTYW + 8 * (st - 1)); }
        }
      }
    }
    TLR(9);
    auto send_ok = [&]() { if (lane == 0) asm volatile("mbarrier.arrive.shared::cluster.b64 _, [%0];" ::"r"(peer + B_SENDOK) : "memory"); };
    if (!keeper) {
#pragma unroll
      for (int s = 0; s < 5; s++) {
        mbar_wait(sb + B_FULL3 + 8 * s, 0);
        if (s == 0) TLR(10);
        g2_stage(dae + 512 * s, s, s < 4 ? 4 : 3, 1);
        if (s == 0) { wg_wait<1>(); send_ok(); }
      }
      nb_arrive(NB_SENT, 256);
      mbar_wait(sb + B_SENDOK, 0);
      wg_wait<0>();
      pin(d);
      TLR(13);
      const uint32_t dst = peer + OFF_RECV + w4 * 4096 + lane * 16;
#pragma unroll
      for (int jj = 0; jj < 8; jj++)
        asm volatile("st.async.shared::cluster.mbarrier::complete_tx::bytes.v4.b32 [%0], {%1, %2, %3, %4}, [%5];"
                     ::"r"(dst + jj * 512), "r"(pack_bf16(d[8 * jj], d[8 * jj + 1])), "r"(pack_bf16(d[8 * jj + 2], d[8 * jj + 3])),
                       "r"(pack_bf16(d[8 * jj + 4], d[8 * jj + 5])), "r"(pack_bf16(d[8 * jj + 6], d[8 * jj + 7])), "r"(peer + B_RECV) : "memory");
      TLR(14);
    } else {
      wg_wait<0>();
      send_ok();
      mbar_wait(sb + B_KH, 0);
      const uint32_t ya = sb + OFF_P + (8 * (mat >> 1) + ii) * 128 + 16 * ((2 * w4 + (mat & 1)) ^ ii);
      const uint32_t ra = sb + OFF_RECV + w4 * 4096 + lane * 16;
      const uint32_t oa = sb + OFF_RECV + w4 * 4096 + (ii + 8 * (mat & 1)) * 128;
      const uint32_t ga = lds32(sb + OFF_GATE + 4 * (16 * w4 + (lane >> 2))), gb = lds32(sb + OFF_GATE + 4 * (16 * w4 + (lane >> 2)) + 32);
      const uint32_t g0 = __byte_perm(ga, 0, 0x1010), g1 = __byte_perm(gb, 0, 0x1010);
      const uint32_t o0 = __byte_perm(ga, 0, 0x3232), o1 = __byte_perm(gb, 0, 0x3232);
      nb_sync(NB_SENT, 256);
      TLR(10);
#pragma unroll
      for (int s = 0; s < 5; s++) g2_stage(dal + 512 * s, s, s < 4 ? 4 : 3, 1);
      TLR(12);
      uint32_t yv[32];
      float4 rv[8];
      mbar_wait(sb + B_YFULL, 0);
#pragma unroll
      for (int jj = 0; jj < YFIRST; jj++) ldsm4t(ya + jj * 2048, yv + 4 * jj);
      mbar_wait(sb + B_RECV, 0);
      TLR(13);
#pragma unroll
      for (int jj = 0; jj < 8; jj++) {
        rv[jj] = ldsf4(ra + jj * 512);
        if (jj >= YFIRST) ldsm4t(ya + jj * 2048, yv + 4 * jj);
      }
      wg_wait<0>();
      pin(d);
      TLR(14);
#pragma unroll
      for (int jj = 0; jj < 8; jj++) {
        const uint32_t r[4] = {__float_as_uint(rv[jj].x), __float_as_uint(rv[jj].y), __float_as_uint(rv[jj].z), __float_as_uint(rv[jj].w)};
#pragma unroll
        for (int e = 0; e < 4; e++) {
          const uint32_t o = (e & 1) ? o1 : o0;
          yv[4 * jj + e] = bfma2((e & 1) ? g1 : g0, yv[4 * jj + e], bmul2(o, badd2(r[e], pack_bf16(d[8 * jj + 2 * e], d[8 * jj + 2 * e + 1]))));
        }
        stsm4(oa + (jj >> 2) * 2048 + 16 * ((2 * (jj & 3) + (mat >> 1)) ^ ii), yv[4 * jj], yv[4 * jj + 1], yv[4 * jj + 2], yv[4 * jj + 3]);
        if ((jj & 3) == 3) {
          fence_async_smem();
          __syncwarp();
          if (elect()) tma3d_store(&tm_out, sb + OFF_RECV + w4 * 4096 + (jj >> 2) * 2048, 0, 64 * tb + 16 * w4, 2 * cq + (jj >> 2));
        }
      }
      if (elect()) {
        asm volatile("cp.async.bulk.commit_group;" ::: "memory");
        asm volatile("cp.async.bulk.wait_group.read 0;" ::: "memory");
      }
      __syncwarp();
      TLR(15);
    }
    TLR_DUMP;
    __syncwarp();
    if (lane == 0) mbar_arrive(sb + B_DONE);
  }
}

typedef CUresult (*EncodeFn)(CUtensorMap*, CUtensorMapDataType, cuuint32_t, void*, const cuuint64_t*, const cuuint64_t*,
                             const cuuint32_t*, const cuuint32_t*, CUtensorMapInterleave, CUtensorMapSwizzle,
                             CUtensorMapL2promotion, CUtensorMapFloatOOBfill);

static void encode(EncodeFn fn, CUtensorMap* m, const void* base, int rank, const cuuint64_t* dims, const cuuint64_t* strides,
                   const cuuint32_t* box, CUtensorMapSwizzle sw) {
  const cuuint32_t es[4] = {1, 1, 1, 1};
  fn(m, CU_TENSOR_MAP_DATA_TYPE_BFLOAT16, rank, const_cast<void*>(base), dims, strides, box, es, CU_TENSOR_MAP_INTERLEAVE_NONE, sw,
     CU_TENSOR_MAP_L2_PROMOTION_L2_128B, CU_TENSOR_MAP_FLOAT_OOB_FILL_NONE);
}

extern "C" void kernel_launch(void* const* d_in, const int* in_sizes, int n_in, void* d_out, int out_size) {
  void* fp = nullptr;
  cudaDriverEntryPointQueryResult qr;
  cudaGetDriverEntryPoint("cuTensorMapEncodeTiled", &fp, cudaEnableDefault, &qr);
  EncodeFn fn = (EncodeFn)fp;
  CUtensorMap tm_x, tm_wg, tm_wg3, tm_wu, tm_wu3, tm_wd, tm_out, tm_u, tm_xp, tm_ul;
  {
    const cuuint64_t dims[2] = {kD, kL}, st[1] = {kD * 2};
    const cuuint32_t box[2] = {32, 128};
    encode(fn, &tm_x, d_in[0], 2, dims, st, box, CU_TENSOR_MAP_SWIZZLE_64B);
  }
  {
    const cuuint64_t dims[3] = {512, kD, 2}, dim3[2] = {kF, kD}, st[2] = {kF * 2, 1024};
    const cuuint32_t box[3] = {64, 32, 2}, box3[2] = {40, 32};
    encode(fn, &tm_wg, d_in[8], 3, dims, st, box, CU_TENSOR_MAP_SWIZZLE_128B);
    encode(fn, &tm_wu, d_in[9], 3, dims, st, box, CU_TENSOR_MAP_SWIZZLE_128B);
    encode(fn, &tm_wg3, d_in[8], 2, dim3, st, box3, CU_TENSOR_MAP_SWIZZLE_128B);
    encode(fn, &tm_wu3, d_in[9], 2, dim3, st, box3, CU_TENSOR_MAP_SWIZZLE_128B);
  }
  {
    const cuuint64_t st[2] = {kD * 2, 128};
    const cuuint32_t box[3] = {64, 64, 2};
    const cuuint64_t dw[3] = {64, kF, 8}, dx[3] = {64, kL, 8};
    encode(fn, &tm_wd, d_in[10], 3, dw, st, box, CU_TENSOR_MAP_SWIZZLE_128B);
    const cuuint32_t boxo[3] = {64, 16, 1};
    encode(fn, &tm_out, d_out, 3, dx, st, boxo, CU_TENSOR_MAP_SWIZZLE_128B);
  }
  {
    void* u = nullptr;
    cudaGetSymbolAddress(&u, g_u);
    const cuuint64_t dims[3] = {1024, 512, 2}, st[2] = {2048, 512 * 2048};
    const cuuint32_t box[3] = {64, 64, 2};
    encode(fn, &tm_u, u, 3, dims, st, box, CU_TENSOR_MAP_SWIZZLE_128B);
    const cuuint64_t diml[4] = {64, 16, 2, 512}, stl[3] = {128, 512 * 2048, 2048};
    const cuuint32_t boxl[4] = {64, 17, 2, 4};
    encode(fn, &tm_ul, u, 4, diml, stl, boxl, CU_TENSOR_MAP_SWIZZLE_NONE);
  }
  {
    const cuuint64_t dims[4] = {kD, 8, 8, 32}, st[3] = {8 * kD * 2, kD * 2, 64 * kD * 2};
    const cuuint32_t box[4] = {64, 8, 8, 2};
    encode(fn, &tm_xp, d_in[0], 4, dims, st, box, CU_TENSOR_MAP_SWIZZLE_128B);
  }
  Params p;
  p.x = (const __nv_bfloat16*)d_in[0];      p.log_a = (const __nv_bfloat16*)d_in[1];
  p.a_im = (const __nv_bfloat16*)d_in[2];   p.c_re = (const __nv_bfloat16*)d_in[3];
  p.c_im = (const __nv_bfloat16*)d_in[4];   p.log_dt = (const __nv_bfloat16*)d_in[5];
  p.d_skip = (const __nv_bfloat16*)d_in[6]; p.w_down = (const __nv_bfloat16*)d_in[10];
  p.gate_w = (const __nv_bfloat16*)d_in[11];
  p.w_gate = (const __nv_bfloat16*)d_in[8]; p.w_up = (const __nv_bfloat16*)d_in[9];
  cudaFuncSetAttribute(gated_mix_kernel, cudaFuncAttributeMaxDynamicSharedMemorySize, SMEM_BYTES);
  gated_mix_kernel<<<132, 512, SMEM_BYTES>>>(p, tm_x, tm_wg, tm_wg3, tm_wu, tm_wu3, tm_wd, tm_out, tm_u, tm_xp, tm_ul);
}
```

```cpp
#include <cuda_runtime.h>
#include <cuda_bf16.h>
#include <cuda_fp16.h>
#include <cuda.h>
#include <stdint.h>

namespace {

constexpr int kL = 2048, kD = 512, kF = 1376;
constexpr int kSkewAt = 1;
constexpr int kConvHead = 6;
constexpr int kG2Head = 3;

constexpr uint32_t SLOT1   = 32768;
constexpr uint32_t OFF_P   = 0;
constexpr uint32_t OFF_W2  = 16384;
constexpr uint32_t OFF_RECV = OFF_W2 + 5 * 16384;
constexpr uint32_t OFF_HE  = 114688;
constexpr uint32_t OFF_A   = 163840;
constexpr uint32_t KT_COPY = 4208;
constexpr uint32_t KT_CH   = 2 * KT_COPY;
constexpr uint32_t OFF_PARK = OFF_A + 16896;
constexpr uint32_t OFF_KS  = OFF_A + 21504;
constexpr uint32_t OFF_KT23 = OFF_KS + 11840;
constexpr uint32_t OFF_GATE = OFF_A + 40960;
constexpr uint32_t KC_CH   = 2048;
constexpr uint32_t UT_PAR  = 2176;
constexpr uint32_t UT_CH   = 2 * UT_PAR;
constexpr uint32_t OFF_UT  = OFF_KS + 28672;
constexpr uint32_t OFF_HL5 = OFF_UT + UT_CH;
constexpr uint32_t OFF_BAR = OFF_UT + 4 * UT_CH;
constexpr uint32_t SMEM_BYTES = OFF_BAR + 512;

constexpr uint32_t B_FULL1 = OFF_BAR, B_RECV = B_FULL1 + 40;
constexpr uint32_t B_EMPTY1 = B_RECV + 8;
constexpr uint32_t B_SENDOK = B_EMPTY1 + 40;
constexpr uint32_t B_G1DONE = B_SENDOK + 8, B_EMPTYW = B_G1DONE + 8, B_C12 = B_EMPTYW + 40;
constexpr uint32_t B_EMPTYH = B_C12 + 8, B_PEMPTY = B_EMPTYH + 40, B_TAB = B_PEMPTY + 32;
constexpr uint32_t B_FULL3 = B_TAB + 16, B_DONE = B_FULL3 + 40;
constexpr uint32_t B_HL = B_DONE + 8, B_HE = B_HL + 48, B_WF = B_HE + 48, B_KH = B_WF + 8;
constexpr uint32_t B_UFULL = B_KH + 8, B_XTFULL = B_UFULL + 8, B_XTREAD = B_XTFULL + 8, B_W5 = B_XTREAD + 8, B_YFULL = B_W5 + 8;
constexpr uint32_t OFF_EPOCH = B_YFULL + 8;
static_assert(OFF_EPOCH + 4 <= SMEM_BYTES && SMEM_BYTES <= 232448 && OFF_UT % 1024 == 0, "shared memory map");

__host__ __device__ constexpr int conv_ch(int c) { return (c + 1) & 3; }

enum { NB_SKEW = 1, NB_H0, NB_H1, NB_GO0, NB_GO1, NB_PFULL0, NB_PFULL1, NB_AUX, NB_UT, NB_KC0, NB_SENT, NB_ST0, NB_ST1, NB_INIT, NB_PAR };

constexpr int FLAG_STRIDE = 32;
constexpr int FL_H = 0, FL_U = 32, FL_Y = 40;

}

__device__ __align__(1024) uint8_t g_h[32 * 88 * 2048];
__device__ __align__(1024) uint8_t g_y[32 * 512 * 128];
__device__ __align__(1024) uint8_t g_u[2 * 512 * 2048];
__device__ __align__(256) uint32_t g_gate[kL];
__device__ uint32_t g_flags[44 * FLAG_STRIDE];

namespace {

__device__ __forceinline__ void mma_x(float (&d)[36], uint32_t alo, uint32_t blo, int scale) {
  asm volatile("{\n.reg .pred p;\n.reg .b64 da, db;\nsetp.ne.b32 p, %38, 0;\nmov.b64 da, {%36, %39};\nmov.b64 db, {%37, %40};\n"
    "wgmma.mma_async.sync.aligned.m64n72k16.f32.bf16.bf16 {%0,%1,%2,%3,%4,%5,%6,%7,%8,%9,%10,%11,%12,%13,%14,%15,%16,%17,%18,%19,%20,%21,%22,%23,%24,%25,%26,%27,%28,%29,%30,%31,%32,%33,%34,%35}, da, db, p, 1, 1, 0, 1;\n}\n"
    : "+f"(d[0]),"+f"(d[1]),"+f"(d[2]),"+f"(d[3]),"+f"(d[4]),"+f"(d[5]),"+f"(d[6]),"+f"(d[7]),"+f"(d[8]),"+f"(d[9]),"+f"(d[10]),"+f"(d[11]),"+f"(d[12]),"+f"(d[13]),"+f"(d[14]),"+f"(d[15]),"+f"(d[16]),"+f"(d[17]),"+f"(d[18]),"+f"(d[19]),"+f"(d[20]),"+f"(d[21]),"+f"(d[22]),"+f"(d[23]),"+f"(d[24]),"+f"(d[25]),"+f"(d[26]),"+f"(d[27]),"+f"(d[28]),"+f"(d[29]),"+f"(d[30]),"+f"(d[31]),"+f"(d[32]),"+f"(d[33]),"+f"(d[34]),"+f"(d[35])
    : "r"(alo), "r"(blo), "r"(scale), "n"(-2147483616), "n"(513));
}
__device__ __forceinline__ void mma_g1(float (&d)[84], uint32_t alo, uint32_t blo, int scale) {
  asm volatile("{\n.reg .pred p;\n.reg .b64 da, db;\nsetp.ne.b32 p, %86, 0;\nmov.b64 da, {%84, %87};\nmov.b64 db, {%85, %88};\n"
    "wgmma.mma_async.sync.aligned.m64n168k16.f32.bf16.bf16 {%0,%1,%2,%3,%4,%5,%6,%7,%8,%9,%10,%11,%12,%13,%14,%15,%16,%17,%18,%19,%20,%21,%22,%23,%24,%25,%26,%27,%28,%29,%30,%31,%32,%33,%34,%35,%36,%37,%38,%39,%40,%41,%42,%43,%44,%45,%46,%47,%48,%49,%50,%51,%52,%53,%54,%55,%56,%57,%58,%59,%60,%61,%62,%63,%64,%65,%66,%67,%68,%69,%70,%71,%72,%73,%74,%75,%76,%77,%78,%79,%80,%81,%82,%83}, da, db, p, 1, 1, 0, 1;\n}\n"
    : "+f"(d[0]),"+f"(d[1]),"+f"(d[2]),"+f"(d[3]),"+f"(d[4]),"+f"(d[5]),"+f"(d[6]),"+f"(d[7]),"+f"(d[8]),"+f"(d[9]),"+f"(d[10]),"+f"(d[11]),"+f"(d[12]),"+f"(d[13]),"+f"(d[14]),"+f"(d[15]),"+f"(d[16]),"+f"(d[17]),"+f"(d[18]),"+f"(d[19]),"+f"(d[20]),"+f"(d[21]),"+f"(d[22]),"+f"(d[23]),"+f"(d[24]),"+f"(d[25]),"+f"(d[26]),"+f"(d[27]),"+f"(d[28]),"+f"(d[29]),"+f"(d[30]),"+f"(d[31]),"+f"(d[32]),"+f"(d[33]),"+f"(d[34]),"+f"(d[35]),"+f"(d[36]),"+f"(d[37]),"+f"(d[38]),"+f"(d[39]),"+f"(d[40]),"+f"(d[41]),"+f"(d[42]),"+f"(d[43]),"+f"(d[44]),"+f"(d[45]),"+f"(d[46]),"+f"(d[47]),"+f"(d[48]),"+f"(d[49]),"+f"(d[50]),"+f"(d[51]),"+f"(d[52]),"+f"(d[53]),"+f"(d[54]),"+f"(d[55]),"+f"(d[56]),"+f"(d[57]),"+f"(d[58]),"+f"(d[59]),"+f"(d[60]),"+f"(d[61]),"+f"(d[62]),"+f"(d[63]),"+f"(d[64]),"+f"(d[65]),"+f"(d[66]),"+f"(d[67]),"+f"(d[68]),"+f"(d[69]),"+f"(d[70]),"+f"(d[71]),"+f"(d[72]),"+f"(d[73]),"+f"(d[74]),"+f"(d[75]),"+f"(d[76]),"+f"(d[77]),"+f"(d[78]),"+f"(d[79]),"+f"(d[80]),"+f"(d[81]),"+f"(d[82]),"+f"(d[83])
    : "r"(alo), "r"(blo), "r"(scale), "n"(-2147483616), "n"(1073741888));
}
__device__ __forceinline__ void mma_g2(float (&d)[64], uint32_t alo, uint32_t blo, int scale) {
  asm volatile("{\n.reg .pred p;\n.reg .b64 da, db;\nsetp.ne.b32 p, %66, 0;\nmov.b64 da, {%64, %67};\nmov.b64 db, {%65, %68};\n"
    "wgmma.mma_async.sync.aligned.m64n128k16.f32.bf16.bf16 {%0,%1,%2,%3,%4,%5,%6,%7,%8,%9,%10,%11,%12,%13,%14,%15,%16,%17,%18,%19,%20,%21,%22,%23,%24,%25,%26,%27,%28,%29,%30,%31,%32,%33,%34,%35,%36,%37,%38,%39,%40,%41,%42,%43,%44,%45,%46,%47,%48,%49,%50,%51,%52,%53,%54,%55,%56,%57,%58,%59,%60,%61,%62,%63}, da, db, p, 1, 1, 0, 1;\n}\n"
    : "+f"(d[0]),"+f"(d[1]),"+f"(d[2]),"+f"(d[3]),"+f"(d[4]),"+f"(d[5]),"+f"(d[6]),"+f"(d[7]),"+f"(d[8]),"+f"(d[9]),"+f"(d[10]),"+f"(d[11]),"+f"(d[12]),"+f"(d[13]),"+f"(d[14]),"+f"(d[15]),"+f"(d[16]),"+f"(d[17]),"+f"(d[18]),"+f"(d[19]),"+f"(d[20]),"+f"(d[21]),"+f"(d[22]),"+f"(d[23]),"+f"(d[24]),"+f"(d[25]),"+f"(d[26]),"+f"(d[27]),"+f"(d[28]),"+f"(d[29]),"+f"(d[30]),"+f"(d[31]),"+f"(d[32]),"+f"(d[33]),"+f"(d[34]),"+f"(d[35]),"+f"(d[36]),"+f"(d[37]),"+f"(d[38]),"+f"(d[39]),"+f"(d[40]),"+f"(d[41]),"+f"(d[42]),"+f"(d[43]),"+f"(d[44]),"+f"(d[45]),"+f"(d[46]),"+f"(d[47]),"+f"(d[48]),"+f"(d[49]),"+f"(d[50]),"+f"(d[51]),"+f"(d[52]),"+f"(d[53]),"+f"(d[54]),"+f"(d[55]),"+f"(d[56]),"+f"(d[57]),"+f"(d[58]),"+f"(d[59]),"+f"(d[60]),"+f"(d[61]),"+f"(d[62]),"+f"(d[63])
    : "r"(alo), "r"(blo), "r"(scale), "n"(8), "n"(1073741888));
}
__device__ __forceinline__ void mma_kgen(float (&d)[24], uint32_t alo, uint32_t blo, int scale) {
  asm volatile("{\n.reg .pred p;\n.reg .b64 da, db;\nsetp.ne.b32 p, %26, 0;\nmov.b64 da, {%24, %27};\nmov.b64 db, {%25, %28};\n"
    "wgmma.mma_async.sync.aligned.m64n48k16.f32.f16.f16 {%0,%1,%2,%3,%4,%5,%6,%7,%8,%9,%10,%11,%12,%13,%14,%15,%16,%17,%18,%19,%20,%21,%22,%23}, da, db, p, 1, 1, 1, 1;\n}\n"
    : "+f"(d[0]),"+f"(d[1]),"+f"(d[2]),"+f"(d[3]),"+f"(d[4]),"+f"(d[5]),"+f"(d[6]),"+f"(d[7]),"+f"(d[8]),"+f"(d[9]),"+f"(d[10]),"+f"(d[11]),"+f"(d[12]),"+f"(d[13]),"+f"(d[14]),"+f"(d[15]),"+f"(d[16]),"+f"(d[17]),"+f"(d[18]),"+f"(d[19]),"+f"(d[20]),"+f"(d[21]),"+f"(d[22]),"+f"(d[23])
    : "r"(alo), "r"(blo), "r"(scale), "n"(128), "n"(128));
}
template<int N> __device__ __forceinline__ void mma_conv(float (&d)[64], uint32_t alo, uint32_t blo, int scale);
template<> __device__ __forceinline__ void mma_conv<8>(float (&d)[64], uint32_t alo, uint32_t blo, int scale) {
  asm volatile("{\n.reg .pred p;\n.reg .b64 da, db;\nsetp.ne.b32 p, %6, 0;\nmov.b64 da, {%4, %7};\nmov.b64 db, {%5, %8};\n"
    "wgmma.mma_async.sync.aligned.m64n8k16.f32.bf16.bf16 {%0,%1,%2,%3}, da, db, p, 1, 1, 1, 0;\n}\n"
    : "+f"(d[0]),"+f"(d[1]),"+f"(d[2]),"+f"(d[3])
    : "r"(alo), "r"(blo), "r"(scale), "n"(1), "n"(8));
}
template<> __device__ __forceinline__ void mma_conv<16>(float (&d)[64], uint32_t alo, uint32_t blo, int scale) {
  asm volatile("{\n.reg .pred p;\n.reg .b64 da, db;\nsetp.ne.b32 p, %10, 0;\nmov.b64 da, {%8, %11};\nmov.b64 db, {%9, %12};\n"
    "wgmma.mma_async.sync.aligned.m64n16k16.f32.bf16.bf16 {%0,%1,%2,%3,%4,%5,%6,%7}, da, db, p, 1, 1, 1, 0;\n}\n"
    : "+f"(d[0]),"+f"(d[1]),"+f"(d[2]),"+f"(d[3]),"+f"(d[4]),"+f"(d[5]),"+f"(d[6]),"+f"(d[7])
    : "r"(alo), "r"(blo), "r"(scale), "n"(1), "n"(8));
}
template<> __device__ __forceinline__ void mma_conv<24>(float (&d)[64], uint32_t alo, uint32_t blo, int scale) {
  asm volatile("{\n.reg .pred p;\n.reg .b64 da, db;\nsetp.ne.b32 p, %14, 0;\nmov.b64 da, {%12, %15};\nmov.b64 db, {%13, %16};\n"
    "wgmma.mma_async.sync.aligned.m64n24k16.f32.bf16.bf16 {%0,%1,%2,%3,%4,%5,%6,%7,%8,%9,%10,%11}, da, db, p, 1, 1, 1, 0;\n}\n"
    : "+f"(d[0]),"+f"(d[1]),"+f"(d[2]),"+f"(d[3]),"+f"(d[4]),"+f"(d[5]),"+f"(d[6]),"+f"(d[7]),"+f"(d[8]),"+f"(d[9]),"+f"(d[10]),"+f"(d[11])
    : "r"(alo), "r"(blo), "r"(scale), "n"(1), "n"(8));
}
template<> __device__ __forceinline__ void mma_conv<32>(float (&d)[64], uint32_t alo, uint32_t blo, int scale) {
  asm volatile("{\n.reg .pred p;\n.reg .b64 da, db;\nsetp.ne.b32 p, %18, 0;\nmov.b64 da, {%16, %19};\nmov.b64 db, {%17, %20};\n"
    "wgmma.mma_async.sync.aligned.m64n32k16.f32.bf16.bf16 {%0,%1,%2,%3,%4,%5,%6,%7,%8,%9,%10,%11,%12,%13,%14,%15}, da, db, p, 1, 1, 1, 0;\n}\n"
    : "+f"(d[0]),"+f"(d[1]),"+f"(d[2]),"+f"(d[3]),"+f"(d[4]),"+f"(d[5]),"+f"(d[6]),"+f"(d[7]),"+f"(d[8]),"+f"(d[9]),"+f"(d[10]),"+f"(d[11]),"+f"(d[12]),"+f"(d[13]),"+f"(d[14]),"+f"(d[15])
    : "r"(alo), "r"(blo), "r"(scale), "n"(1), "n"(8));
}
template<> __device__ __forceinline__ void mma_conv<40>(float (&d)[64], uint32_t alo, uint32_t blo, int scale) {
  asm volatile("{\n.reg .pred p;\n.reg .b64 da, db;\nsetp.ne.b32 p, %22, 0;\nmov.b64 da, {%20, %23};\nmov.b64 db, {%21, %24};\n"
    "wgmma.mma_async.sync.aligned.m64n40k16.f32.bf16.bf16 {%0,%1,%2,%3,%4,%5,%6,%7,%8,%9,%10,%11,%12,%13,%14,%15,%16,%17,%18,%19}, da, db, p, 1, 1, 1, 0;\n}\n"
    : "+f"(d[0]),"+f"(d[1]),"+f"(d[2]),"+f"(d[3]),"+f"(d[4]),"+f"(d[5]),"+f"(d[6]),"+f"(d[7]),"+f"(d[8]),"+f"(d[9]),"+f"(d[10]),"+f"(d[11]),"+f"(d[12]),"+f"(d[13]),"+f"(d[14]),"+f"(d[15]),"+f"(d[16]),"+f"(d[17]),"+f"(d[18]),"+f"(d[19])
    : "r"(alo), "r"(blo), "r"(scale), "n"(1), "n"(8));
}
template<> __device__ __forceinline__ void mma_conv<48>(float (&d)[64], uint32_t alo, uint32_t blo, int scale) {
  asm volatile("{\n.reg .pred p;\n.reg .b64 da, db;\nsetp.ne.b32 p, %26, 0;\nmov.b64 da, {%24, %27};\nmov.b64 db, {%25, %28};\n"
    "wgmma.mma_async.sync.aligned.m64n48k16.f32.bf16.bf16 {%0,%1,%2,%3,%4,%5,%6,%7,%8,%9,%10,%11,%12,%13,%14,%15,%16,%17,%18,%19,%20,%21,%22,%23}, da, db, p, 1, 1, 1, 0;\n}\n"
    : "+f"(d[0]),"+f"(d[1]),"+f"(d[2]),"+f"(d[3]),"+f"(d[4]),"+f"(d[5]),"+f"(d[6]),"+f"(d[7]),"+f"(d[8]),"+f"(d[9]),"+f"(d[10]),"+f"(d[11]),"+f"(d[12]),"+f"(d[13]),"+f"(d[14]),"+f"(d[15]),"+f"(d[16]),"+f"(d[17]),"+f"(d[18]),"+f"(d[19]),"+f"(d[20]),"+f"(d[21]),"+f"(d[22]),"+f"(d[23])
    : "r"(alo), "r"(blo), "r"(scale), "n"(1), "n"(8));
}
template<> __device__ __forceinline__ void mma_conv<56>(float (&d)[64], uint32_t alo, uint32_t blo, int scale) {
  asm volatile("{\n.reg .pred p;\n.reg .b64 da, db;\nsetp.ne.b32 p, %30, 0;\nmov.b64 da, {%28, %31};\nmov.b64 db, {%29, %32};\n"
    "wgmma.mma_async.sync.aligned.m64n56k16.f32.bf16.bf16 {%0,%1,%2,%3,%4,%5,%6,%7,%8,%9,%10,%11,%12,%13,%14,%15,%16,%17,%18,%19,%20,%21,%22,%23,%24,%25,%26,%27}, da, db, p, 1, 1, 1, 0;\n}\n"
    : "+f"(d[0]),"+f"(d[1]),"+f"(d[2]),"+f"(d[3]),"+f"(d[4]),"+f"(d[5]),"+f"(d[6]),"+f"(d[7]),"+f"(d[8]),"+f"(d[9]),"+f"(d[10]),"+f"(d[11]),"+f"(d[12]),"+f"(d[13]),"+f"(d[14]),"+f"(d[15]),"+f"(d[16]),"+f"(d[17]),"+f"(d[18]),"+f"(d[19]),"+f"(d[20]),"+f"(d[21]),"+f"(d[22]),"+f"(d[23]),"+f"(d[24]),"+f"(d[25]),"+f"(d[26]),"+f"(d[27])
    : "r"(alo), "r"(blo), "r"(scale), "n"(1), "n"(8));
}
template<> __device__ __forceinline__ void mma_conv<64>(float (&d)[64], uint32_t alo, uint32_t blo, int scale) {
  asm volatile("{\n.reg .pred p;\n.reg .b64 da, db;\nsetp.ne.b32 p, %34, 0;\nmov.b64 da, {%32, %35};\nmov.b64 db, {%33, %36};\n"
    "wgmma.mma_async.sync.aligned.m64n64k16.f32.bf16.bf16 {%0,%1,%2,%3,%4,%5,%6,%7,%8,%9,%10,%11,%12,%13,%14,%15,%16,%17,%18,%19,%20,%21,%22,%23,%24,%25,%26,%27,%28,%29,%30,%31}, da, db, p, 1, 1, 1, 0;\n}\n"
    : "+f"(d[0]),"+f"(d[1]),"+f"(d[2]),"+f"(d[3]),"+f"(d[4]),"+f"(d[5]),"+f"(d[6]),"+f"(d[7]),"+f"(d[8]),"+f"(d[9]),"+f"(d[10]),"+f"(d[11]),"+f"(d[12]),"+f"(d[13]),"+f"(d[14]),"+f"(d[15]),"+f"(d[16]),"+f"(d[17]),"+f"(d[18]),"+f"(d[19]),"+f"(d[20]),"+f"(d[21]),"+f"(d[22]),"+f"(d[23]),"+f"(d[24]),"+f"(d[25]),"+f"(d[26]),"+f"(d[27]),"+f"(d[28]),"+f"(d[29]),"+f"(d[30]),"+f"(d[31])
    : "r"(alo), "r"(blo), "r"(scale), "n"(1), "n"(8));
}
template<> __device__ __forceinline__ void mma_conv<72>(float (&d)[64], uint32_t alo, uint32_t blo, int scale) {
  asm volatile("{\n.reg .pred p;\n.reg .b64 da, db;\nsetp.ne.b32 p, %38, 0;\nmov.b64 da, {%36, %39};\nmov.b64 db, {%37, %40};\n"
    "wgmma.mma_async.sync.aligned.m64n72k16.f32.bf16.bf16 {%0,%1,%2,%3,%4,%5,%6,%7,%8,%9,%10,%11,%12,%13,%14,%15,%16,%17,%18,%19,%20,%21,%22,%23,%24,%25,%26,%27,%28,%29,%30,%31,%32,%33,%34,%35}, da, db, p, 1, 1, 1, 0;\n}\n"
    : "+f"(d[0]),"+f"(d[1]),"+f"(d[2]),"+f"(d[3]),"+f"(d[4]),"+f"(d[5]),"+f"(d[6]),"+f"(d[7]),"+f"(d[8]),"+f"(d[9]),"+f"(d[10]),"+f"(d[11]),"+f"(d[12]),"+f"(d[13]),"+f"(d[14]),"+f"(d[15]),"+f"(d[16]),"+f"(d[17]),"+f"(d[18]),"+f"(d[19]),"+f"(d[20]),"+f"(d[21]),"+f"(d[22]),"+f"(d[23]),"+f"(d[24]),"+f"(d[25]),"+f"(d[26]),"+f"(d[27]),"+f"(d[28]),"+f"(d[29]),"+f"(d[30]),"+f"(d[31]),"+f"(d[32]),"+f"(d[33]),"+f"(d[34]),"+f"(d[35])
    : "r"(alo), "r"(blo), "r"(scale), "n"(1), "n"(8));
}
template<> __device__ __forceinline__ void mma_conv<80>(float (&d)[64], uint32_t alo, uint32_t blo, int scale) {
  asm volatile("{\n.reg .pred p;\n.reg .b64 da, db;\nsetp.ne.b32 p, %42, 0;\nmov.b64 da, {%40, %43};\nmov.b64 db, {%41, %44};\n"
    "wgmma.mma_async.sync.aligned.m64n80k16.f32.bf16.bf16 {%0,%1,%2,%3,%4,%5,%6,%7,%8,%9,%10,%11,%12,%13,%14,%15,%16,%17,%18,%19,%20,%21,%22,%23,%24,%25,%26,%27,%28,%29,%30,%31,%32,%33,%34,%35,%36,%37,%38,%39}, da, db, p, 1, 1, 1, 0;\n}\n"
    : "+f"(d[0]),"+f"(d[1]),"+f"(d[2]),"+f"(d[3]),"+f"(d[4]),"+f"(d[5]),"+f"(d[6]),"+f"(d[7]),"+f"(d[8]),"+f"(d[9]),"+f"(d[10]),"+f"(d[11]),"+f"(d[12]),"+f"(d[13]),"+f"(d[14]),"+f"(d[15]),"+f"(d[16]),"+f"(d[17]),"+f"(d[18]),"+f"(d[19]),"+f"(d[20]),"+f"(d[21]),"+f"(d[22]),"+f"(d[23]),"+f"(d[24]),"+f"(d[25]),"+f"(d[26]),"+f"(d[27]),"+f"(d[28]),"+f"(d[29]),"+f"(d[30]),"+f"(d[31]),"+f"(d[32]),"+f"(d[33]),"+f"(d[34]),"+f"(d[35]),"+f"(d[36]),"+f"(d[37]),"+f"(d[38]),"+f"(d[39])
    : "r"(alo), "r"(blo), "r"(scale), "n"(1), "n"(8));
}
template<> __device__ __forceinline__ void mma_conv<88>(float (&d)[64], uint32_t alo, uint32_t blo, int scale) {
  asm volatile("{\n.reg .pred p;\n.reg .b64 da, db;\nsetp.ne.b32 p, %46, 0;\nmov.b64 da, {%44, %47};\nmov.b64 db, {%45, %48};\n"
    "wgmma.mma_async.sync.aligned.m64n88k16.f32.bf16.bf16 {%0,%1,%2,%3,%4,%5,%6,%7,%8,%9,%10,%11,%12,%13,%14,%15,%16,%17,%18,%19,%20,%21,%22,%23,%24,%25,%26,%27,%28,%29,%30,%31,%32,%33,%34,%35,%36,%37,%38,%39,%40,%41,%42,%43}, da, db, p, 1, 1, 1, 0;\n}\n"
    : "+f"(d[0]),"+f"(d[1]),"+f"(d[2]),"+f"(d[3]),"+f"(d[4]),"+f"(d[5]),"+f"(d[6]),"+f"(d[7]),"+f"(d[8]),"+f"(d[9]),"+f"(d[10]),"+f"(d[11]),"+f"(d[12]),"+f"(d[13]),"+f"(d[14]),"+f"(d[15]),"+f"(d[16]),"+f"(d[17]),"+f"(d[18]),"+f"(d[19]),"+f"(d[20]),"+f"(d[21]),"+f"(d[22]),"+f"(d[23]),"+f"(d[24]),"+f"(d[25]),"+f"(d[26]),"+f"(d[27]),"+f"(d[28]),"+f"(d[29]),"+f"(d[30]),"+f"(d[31]),"+f"(d[32]),"+f"(d[33]),"+f"(d[34]),"+f"(d[35]),"+f"(d[36]),"+f"(d[37]),"+f"(d[38]),"+f"(d[39]),"+f"(d[40]),"+f"(d[41]),"+f"(d[42]),"+f"(d[43])
    : "r"(alo), "r"(blo), "r"(scale), "n"(1), "n"(8));
}
template<> __device__ __forceinline__ void mma_conv<96>(float (&d)[64], uint32_t alo, uint32_t blo, int scale) {
  asm volatile("{\n.reg .pred p;\n.reg .b64 da, db;\nsetp.ne.b32 p, %50, 0;\nmov.b64 da, {%48, %51};\nmov.b64 db, {%49, %52};\n"
    "wgmma.mma_async.sync.aligned.m64n96k16.f32.bf16.bf16 {%0,%1,%2,%3,%4,%5,%6,%7,%8,%9,%10,%11,%12,%13,%14,%15,%16,%17,%18,%19,%20,%21,%22,%23,%24,%25,%26,%27,%28,%29,%30,%31,%32,%33,%34,%35,%36,%37,%38,%39,%40,%41,%42,%43,%44,%45,%46,%47}, da, db, p, 1, 1, 1, 0;\n}\n"
    : "+f"(d[0]),"+f"(d[1]),"+f"(d[2]),"+f"(d[3]),"+f"(d[4]),"+f"(d[5]),"+f"(d[6]),"+f"(d[7]),"+f"(d[8]),"+f"(d[9]),"+f"(d[10]),"+f"(d[11]),"+f"(d[12]),"+f"(d[13]),"+f"(d[14]),"+f"(d[15]),"+f"(d[16]),"+f"(d[17]),"+f"(d[18]),"+f"(d[19]),"+f"(d[20]),"+f"(d[21]),"+f"(d[22]),"+f"(d[23]),"+f"(d[24]),"+f"(d[25]),"+f"(d[26]),"+f"(d[27]),"+f"(d[28]),"+f"(d[29]),"+f"(d[30]),"+f"(d[31]),"+f"(d[32]),"+f"(d[33]),"+f"(d[34]),"+f"(d[35]),"+f"(d[36]),"+f"(d[37]),"+f"(d[38]),"+f"(d[39]),"+f"(d[40]),"+f"(d[41]),"+f"(d[42]),"+f"(d[43]),"+f"(d[44]),"+f"(d[45]),"+f"(d[46]),"+f"(d[47])
    : "r"(alo), "r"(blo), "r"(scale), "n"(1), "n"(8));
}
template<> __device__ __forceinline__ void mma_conv<104>(float (&d)[64], uint32_t alo, uint32_t blo, int scale) {
  asm volatile("{\n.reg .pred p;\n.reg .b64 da, db;\nsetp.ne.b32 p, %54, 0;\nmov.b64 da, {%52, %55};\nmov.b64 db, {%53, %56};\n"
    "wgmma.mma_async.sync.aligned.m64n104k16.f32.bf16.bf16 {%0,%1,%2,%3,%4,%5,%6,%7,%8,%9,%10,%11,%12,%13,%14,%15,%16,%17,%18,%19,%20,%21,%22,%23,%24,%25,%26,%27,%28,%29,%30,%31,%32,%33,%34,%35,%36,%37,%38,%39,%40,%41,%42,%43,%44,%45,%46,%47,%48,%49,%50,%51}, da, db, p, 1, 1, 1, 0;\n}\n"
    : "+f"(d[0]),"+f"(d[1]),"+f"(d[2]),"+f"(d[3]),"+f"(d[4]),"+f"(d[5]),"+f"(d[6]),"+f"(d[7]),"+f"(d[8]),"+f"(d[9]),"+f"(d[10]),"+f"(d[11]),"+f"(d[12]),"+f"(d[13]),"+f"(d[14]),"+f"(d[15]),"+f"(d[16]),"+f"(d[17]),"+f"(d[18]),"+f"(d[19]),"+f"(d[20]),"+f"(d[21]),"+f"(d[22]),"+f"(d[23]),"+f"(d[24]),"+f"(d[25]),"+f"(d[26]),"+f"(d[27]),"+f"(d[28]),"+f"(d[29]),"+f"(d[30]),"+f"(d[31]),"+f"(d[32]),"+f"(d[33]),"+f"(d[34]),"+f"(d[35]),"+f"(d[36]),"+f"(d[37]),"+f"(d[38]),"+f"(d[39]),"+f"(d[40]),"+f"(d[41]),"+f"(d[42]),"+f"(d[43]),"+f"(d[44]),"+f"(d[45]),"+f"(d[46]),"+f"(d[47]),"+f"(d[48]),"+f"(d[49]),"+f"(d[50]),"+f"(d[51])
    : "r"(alo), "r"(blo), "r"(scale), "n"(1), "n"(8));
}
template<> __device__ __forceinline__ void mma_conv<112>(float (&d)[64], uint32_t alo, uint32_t blo, int scale) {
  asm volatile("{\n.reg .pred p;\n.reg .b64 da, db;\nsetp.ne.b32 p, %58, 0;\nmov.b64 da, {%56, %59};\nmov.b64 db, {%57, %60};\n"
    "wgmma.mma_async.sync.aligned.m64n112k16.f32.bf16.bf16 {%0,%1,%2,%3,%4,%5,%6,%7,%8,%9,%10,%11,%12,%13,%14,%15,%16,%17,%18,%19,%20,%21,%22,%23,%24,%25,%26,%27,%28,%29,%30,%31,%32,%33,%34,%35,%36,%37,%38,%39,%40,%41,%42,%43,%44,%45,%46,%47,%48,%49,%50,%51,%52,%53,%54,%55}, da, db, p, 1, 1, 1, 0;\n}\n"
    : "+f"(d[0]),"+f"(d[1]),"+f"(d[2]),"+f"(d[3]),"+f"(d[4]),"+f"(d[5]),"+f"(d[6]),"+f"(d[7]),"+f"(d[8]),"+f"(d[9]),"+f"(d[10]),"+f"(d[11]),"+f"(d[12]),"+f"(d[13]),"+f"(d[14]),"+f"(d[15]),"+f"(d[16]),"+f"(d[17]),"+f"(d[18]),"+f"(d[19]),"+f"(d[20]),"+f"(d[21]),"+f"(d[22]),"+f"(d[23]),"+f"(d[24]),"+f"(d[25]),"+f"(d[26]),"+f"(d[27]),"+f"(d[28]),"+f"(d[29]),"+f"(d[30]),"+f"(d[31]),"+f"(d[32]),"+f"(d[33]),"+f"(d[34]),"+f"(d[35]),"+f"(d[36]),"+f"(d[37]),"+f"(d[38]),"+f"(d[39]),"+f"(d[40]),"+f"(d[41]),"+f"(d[42]),"+f"(d[43]),"+f"(d[44]),"+f"(d[45]),"+f"(d[46]),"+f"(d[47]),"+f"(d[48]),"+f"(d[49]),"+f"(d[50]),"+f"(d[51]),"+f"(d[52]),"+f"(d[53]),"+f"(d[54]),"+f"(d[55])
    : "r"(alo), "r"(blo), "r"(scale), "n"(1), "n"(8));
}
template<> __device__ __forceinline__ void mma_conv<120>(float (&d)[64], uint32_t alo, uint32_t blo, int scale) {
  asm volatile("{\n.reg .pred p;\n.reg .b64 da, db;\nsetp.ne.b32 p, %62, 0;\nmov.b64 da, {%60, %63};\nmov.b64 db, {%61, %64};\n"
    "wgmma.mma_async.sync.aligned.m64n120k16.f32.bf16.bf16 {%0,%1,%2,%3,%4,%5,%6,%7,%8,%9,%10,%11,%12,%13,%14,%15,%16,%17,%18,%19,%20,%21,%22,%23,%24,%25,%26,%27,%28,%29,%30,%31,%32,%33,%34,%35,%36,%37,%38,%39,%40,%41,%42,%43,%44,%45,%46,%47,%48,%49,%50,%51,%52,%53,%54,%55,%56,%57,%58,%59}, da, db, p, 1, 1, 1, 0;\n}\n"
    : "+f"(d[0]),"+f"(d[1]),"+f"(d[2]),"+f"(d[3]),"+f"(d[4]),"+f"(d[5]),"+f"(d[6]),"+f"(d[7]),"+f"(d[8]),"+f"(d[9]),"+f"(d[10]),"+f"(d[11]),"+f"(d[12]),"+f"(d[13]),"+f"(d[14]),"+f"(d[15]),"+f"(d[16]),"+f"(d[17]),"+f"(d[18]),"+f"(d[19]),"+f"(d[20]),"+f"(d[21]),"+f"(d[22]),"+f"(d[23]),"+f"(d[24]),"+f"(d[25]),"+f"(d[26]),"+f"(d[27]),"+f"(d[28]),"+f"(d[29]),"+f"(d[30]),"+f"(d[31]),"+f"(d[32]),"+f"(d[33]),"+f"(d[34]),"+f"(d[35]),"+f"(d[36]),"+f"(d[37]),"+f"(d[38]),"+f"(d[39]),"+f"(d[40]),"+f"(d[41]),"+f"(d[42]),"+f"(d[43]),"+f"(d[44]),"+f"(d[45]),"+f"(d[46]),"+f"(d[47]),"+f"(d[48]),"+f"(d[49]),"+f"(d[50]),"+f"(d[51]),"+f"(d[52]),"+f"(d[53]),"+f"(d[54]),"+f"(d[55]),"+f"(d[56]),"+f"(d[57]),"+f"(d[58]),"+f"(d[59])
    : "r"(alo), "r"(blo), "r"(scale), "n"(1), "n"(8));
}
template<> __device__ __forceinline__ void mma_conv<128>(float (&d)[64], uint32_t alo, uint32_t blo, int scale) {
  asm volatile("{\n.reg .pred p;\n.reg .b64 da, db;\nsetp.ne.b32 p, %66, 0;\nmov.b64 da, {%64, %67};\nmov.b64 db, {%65, %68};\n"
    "wgmma.mma_async.sync.aligned.m64n128k16.f32.bf16.bf16 {%0,%1,%2,%3,%4,%5,%6,%7,%8,%9,%10,%11,%12,%13,%14,%15,%16,%17,%18,%19,%20,%21,%22,%23,%24,%25,%26,%27,%28,%29,%30,%31,%32,%33,%34,%35,%36,%37,%38,%39,%40,%41,%42,%43,%44,%45,%46,%47,%48,%49,%50,%51,%52,%53,%54,%55,%56,%57,%58,%59,%60,%61,%62,%63}, da, db, p, 1, 1, 1, 0;\n}\n"
    : "+f"(d[0]),"+f"(d[1]),"+f"(d[2]),"+f"(d[3]),"+f"(d[4]),"+f"(d[5]),"+f"(d[6]),"+f"(d[7]),"+f"(d[8]),"+f"(d[9]),"+f"(d[10]),"+f"(d[11]),"+f"(d[12]),"+f"(d[13]),"+f"(d[14]),"+f"(d[15]),"+f"(d[16]),"+f"(d[17]),"+f"(d[18]),"+f"(d[19]),"+f"(d[20]),"+f"(d[21]),"+f"(d[22]),"+f"(d[23]),"+f"(d[24]),"+f"(d[25]),"+f"(d[26]),"+f"(d[27]),"+f"(d[28]),"+f"(d[29]),"+f"(d[30]),"+f"(d[31]),"+f"(d[32]),"+f"(d[33]),"+f"(d[34]),"+f"(d[35]),"+f"(d[36]),"+f"(d[37]),"+f"(d[38]),"+f"(d[39]),"+f"(d[40]),"+f"(d[41]),"+f"(d[42]),"+f"(d[43]),"+f"(d[44]),"+f"(d[45]),"+f"(d[46]),"+f"(d[47]),"+f"(d[48]),"+f"(d[49]),"+f"(d[50]),"+f"(d[51]),"+f"(d[52]),"+f"(d[53]),"+f"(d[54]),"+f"(d[55]),"+f"(d[56]),"+f"(d[57]),"+f"(d[58]),"+f"(d[59]),"+f"(d[60]),"+f"(d[61]),"+f"(d[62]),"+f"(d[63])
    : "r"(alo), "r"(blo), "r"(scale), "n"(1), "n"(8));
}

__device__ __forceinline__ void wg_fence() { asm volatile("wgmma.fence.sync.aligned;" ::: "memory"); }
__device__ __forceinline__ void wg_commit() { asm volatile("wgmma.commit_group.sync.aligned;" ::: "memory"); }
template <int N> __device__ __forceinline__ void wg_wait() { asm volatile("wgmma.wait_group.sync.aligned %0;" ::"n"(N) : "memory"); }
template <int N> __device__ __forceinline__ void pin(float (&d)[N]) {
#pragma unroll
  for (int i = 0; i < N; i++) asm volatile("" : "+f"(d[i])::"memory");
}

__device__ __forceinline__ void mbar_init(uint32_t b, int c) { asm volatile("mbarrier.init.shared::cta.b64 [%0], %1;" ::"r"(b), "r"(c) : "memory"); }
__device__ __forceinline__ void mbar_arrive(uint32_t b) { asm volatile("mbarrier.arrive.shared::cta.b64 _, [%0];" ::"r"(b) : "memory"); }
__device__ __forceinline__ void mbar_expect(uint32_t b, uint32_t bytes) { asm volatile("mbarrier.arrive.expect_tx.shared::cta.b64 _, [%0], %1;" ::"r"(b), "r"(bytes) : "memory"); }
__device__ __forceinline__ void mbar_wait(uint32_t b, uint32_t parity) {
  asm volatile(
      "{\n.reg .pred p;\n.reg .u32 n;\n"
      "mbarrier.try_wait.parity.shared::cta.b64 p, [%0], %1;\n@p bra DONE;\nmov.u32 n, 0;\n"
      "W:\nmbarrier.try_wait.parity.shared::cta.b64 p, [%0], %1, 2000;\n@p bra DONE;\n"
      "add.u32 n, n, 1;\nsetp.lt.u32 p, n, 1000000;\n@p bra W;\ntrap;\nDONE:\n}\n" ::"r"(b), "r"(parity) : "memory");
}
__device__ __forceinline__ void cluster_wait() { asm volatile("barrier.cluster.wait.aligned;" ::: "memory"); }
__device__ __forceinline__ void nb_sync(int id, int n) { asm volatile("bar.sync %0, %1;" ::"r"(id), "r"(n) : "memory"); }
__device__ __forceinline__ void nb_sync_if(int p, int id, int n) {
  asm volatile("{\n.reg .pred p;\nsetp.ne.b32 p, %2, 0;\n@p bar.sync %0, %1;\n}\n" ::"r"(id), "r"(n), "r"(p) : "memory");
}
__device__ __forceinline__ void nb_arrive(int id, int n) { asm volatile("bar.arrive %0, %1;" ::"r"(id), "r"(n) : "memory"); }
__device__ __forceinline__ void fence_async_smem() { asm volatile("fence.proxy.async.shared::cta;" ::: "memory"); }
__device__ __forceinline__ void fence_async_all() { asm volatile("fence.proxy.async;" ::: "memory"); }

__device__ __forceinline__ void flag_signal(int f, uint32_t inc) {
  fence_async_all();
  asm volatile("red.relaxed.gpu.global.add.u32 [%0], %1;" ::"l"(g_flags + f * FLAG_STRIDE), "r"(inc) : "memory");
}
__device__ __forceinline__ uint32_t flag_peek(const uint32_t* f) {
  uint32_t v;
  asm volatile("ld.relaxed.gpu.global.u32 %0, [%1];" : "=r"(v) : "l"(f) : "memory");
  return v;
}
__device__ __forceinline__ void flag_wait(int idx, uint32_t target) {
  const uint32_t* f = g_flags + idx * FLAG_STRIDE;
#pragma unroll 1
  for (int i = 0; (int32_t)(flag_peek(f) - target) < 0; i++)
    if (i == 20000000) __trap();
  asm volatile("fence.acquire.gpu;" ::: "memory");
  asm volatile("fence.proxy.async.global;" ::: "memory");
}

__device__ __forceinline__ void tma2d(uint32_t dst, const CUtensorMap* m, uint32_t bar, int c0, int c1) {
  asm volatile("cp.async.bulk.tensor.2d.shared::cluster.global.mbarrier::complete_tx::bytes [%0], [%1, {%3, %4}], [%2];"
               ::"r"(dst), "l"(m), "r"(bar), "r"(c0), "r"(c1) : "memory");
}
__device__ __forceinline__ void tma3d(uint32_t dst, const CUtensorMap* m, uint32_t bar, int c0, int c1, int c2) {
  asm volatile("cp.async.bulk.tensor.3d.shared::cluster.global.mbarrier::complete_tx::bytes [%0], [%1, {%3, %4, %5}], [%2];"
               ::"r"(dst), "l"(m), "r"(bar), "r"(c0), "r"(c1), "r"(c2) : "memory");
}
__device__ __forceinline__ void tma2d_pair(uint32_t dst, const CUtensorMap* m, uint32_t bar, int c0, int c1) {
  asm volatile("cp.async.bulk.tensor.2d.shared::cluster.global.mbarrier::complete_tx::bytes.multicast::cluster [%0], [%1, {%3, %4}], [%2], %5;"
               ::"r"(dst), "l"(m), "r"(bar), "r"(c0), "r"(c1), "h"((uint16_t)3) : "memory");
}
__device__ __forceinline__ void tma3d_pair(uint32_t dst, const CUtensorMap* m, uint32_t bar, int c0, int c1, int c2) {
  asm volatile("cp.async.bulk.tensor.3d.shared::cluster.global.mbarrier::complete_tx::bytes.multicast::cluster [%0], [%1, {%3, %4, %5}], [%2], %6;"
               ::"r"(dst), "l"(m), "r"(bar), "r"(c0), "r"(c1), "r"(c2), "h"((uint16_t)3) : "memory");
}
__device__ __forceinline__ void mbar_arrive_cluster(uint32_t b) { asm volatile("mbarrier.arrive.shared::cluster.b64 _, [%0];" ::"r"(b) : "memory"); }
__device__ __forceinline__ void tma4d(uint32_t dst, const CUtensorMap* m, uint32_t bar, int c0, int c1, int c2, int c3) {
  asm volatile("cp.async.bulk.tensor.4d.shared::cluster.global.mbarrier::complete_tx::bytes [%0], [%1, {%3, %4, %5, %6}], [%2];"
               ::"r"(dst), "l"(m), "r"(bar), "r"(c0), "r"(c1), "r"(c2), "r"(c3) : "memory");
}
__device__ __forceinline__ void tma3d_store(const CUtensorMap* m, uint32_t src, int c0, int c1, int c2) {
  asm volatile("cp.async.bulk.tensor.3d.global.shared::cta.bulk_group [%0, {%2, %3, %4}], [%1];"
               ::"l"(m), "r"(src), "r"(c0), "r"(c1), "r"(c2) : "memory");
}
__device__ __forceinline__ void bulk_load(uint32_t dst, const void* src, uint32_t bytes, uint32_t bar) {
  asm volatile("cp.async.bulk.shared::cluster.global.mbarrier::complete_tx::bytes [%0], [%1], %2, [%3];"
               ::"r"(dst), "l"(src), "r"(bytes), "r"(bar) : "memory");
}
__device__ __forceinline__ void cp_async16(uint32_t dst, const void* src) {
  asm volatile("cp.async.cg.shared.global [%0], [%1], 16;" ::"r"(dst), "l"(src) : "memory");
}
__device__ __forceinline__ int selp(int a, int b, bool c) {
  int r;
  asm("{\n.reg .pred p;\nsetp.ne.b32 p, %3, 0;\nselp.b32 %0, %1, %2, p;\n}\n" : "=r"(r) : "r"(a), "r"(b), "r"((int)c));
  return r;
}
template <int FROM, int TO> __device__ __forceinline__ void init_barriers(uint32_t base) {
#pragma unroll
  for (int i = FROM; i < TO; i++) mbar_init(base + 8 * i, i < 6 ? 1 : i < 11 ? 16 : i < 19 ? 8 : i < 30 ? 4 : i < 35 ? 2 : i == 35 ? 15 : 1);
}
__device__ __forceinline__ void sched_fence(uint32_t v, uint32_t other) {
  asm volatile("{\n.reg .pred p;\nsetp.ne.u32 p, %0, %1;\n@p bra OK;\ntrap;\nOK:\n}\n" ::"r"(v), "r"(other) : "memory");
}
__device__ __forceinline__ bool elect() {
  uint32_t p;
  asm volatile("{\n.reg .pred p;\nelect.sync _|p, 0xffffffff;\nselp.b32 %0, 1, 0, p;\n}\n" : "=r"(p));
  return p;
}

__device__ __forceinline__ uint32_t pack_bf16(float lo, float hi) { uint32_t r; asm("cvt.rn.bf16x2.f32 %0, %1, %2;" : "=r"(r) : "f"(hi), "f"(lo)); return r; }
__device__ __forceinline__ uint32_t pack_f16(float lo, float hi) { uint32_t r; asm("cvt.rn.f16x2.f32 %0, %1, %2;" : "=r"(r) : "f"(hi), "f"(lo)); return r; }
__device__ __forceinline__ uint32_t bmul2(uint32_t a, uint32_t b) { uint32_t r; asm("mul.rn.bf16x2 %0, %1, %2;" : "=r"(r) : "r"(a), "r"(b)); return r; }
__device__ __forceinline__ uint32_t badd2(uint32_t a, uint32_t b) { uint32_t r; asm("add.rn.bf16x2 %0, %1, %2;" : "=r"(r) : "r"(a), "r"(b)); return r; }
__device__ __forceinline__ uint32_t bfma2(uint32_t a, uint32_t b, uint32_t c) { uint32_t r; asm("fma.rn.bf16x2 %0, %1, %2, %3;" : "=r"(r) : "r"(a), "r"(b), "r"(c)); return r; }
__device__ __forceinline__ float bf_lo(uint32_t w) { return __uint_as_float(w << 16); }
__device__ __forceinline__ float bf_hi(uint32_t w) { return __uint_as_float(w & 0xffff0000u); }
__device__ __forceinline__ float bf_round(float v) { return __bfloat162float(__float2bfloat16_rn(v)); }

__device__ __forceinline__ void sts128(uint32_t a, uint32_t x, uint32_t y, uint32_t z, uint32_t w) { asm volatile("st.shared.v4.u32 [%0], {%1, %2, %3, %4};" ::"r"(a), "r"(x), "r"(y), "r"(z), "r"(w) : "memory"); }
__device__ __forceinline__ void sts32(uint32_t a, uint32_t x) { asm volatile("st.shared.u32 [%0], %1;" ::"r"(a), "r"(x) : "memory"); }
__device__ __forceinline__ void sts16(uint32_t a, uint32_t x) { asm volatile("st.shared.u16 [%0], %1;" ::"r"(a), "h"((uint16_t)x) : "memory"); }
__device__ __forceinline__ void stsf(uint32_t a, float x) { asm volatile("st.shared.f32 [%0], %1;" ::"r"(a), "f"(x) : "memory"); }
__device__ __forceinline__ uint32_t lds32(uint32_t a) { uint32_t v; asm volatile("ld.shared.u32 %0, [%1];" : "=r"(v) : "r"(a) : "memory"); return v; }
__device__ __forceinline__ uint32_t lds16(uint32_t a) { uint16_t v; asm volatile("ld.shared.u16 %0, [%1];" : "=h"(v) : "r"(a) : "memory"); return v; }
__device__ __forceinline__ float ldsf(uint32_t a) { float v; asm volatile("ld.shared.f32 %0, [%1];" : "=f"(v) : "r"(a) : "memory"); return v; }
__device__ __forceinline__ float2 ldsf2(uint32_t a) { float2 v; asm volatile("ld.shared.v2.f32 {%0, %1}, [%2];" : "=f"(v.x), "=f"(v.y) : "r"(a) : "memory"); return v; }
__device__ __forceinline__ float4 ldsf4(uint32_t a) { float4 v; asm volatile("ld.shared.v4.f32 {%0, %1, %2, %3}, [%4];" : "=f"(v.x), "=f"(v.y), "=f"(v.z), "=f"(v.w) : "r"(a) : "memory"); return v; }
__device__ __forceinline__ void stsm4(uint32_t a, uint32_t r0, uint32_t r1, uint32_t r2, uint32_t r3) { asm volatile("stmatrix.sync.aligned.m8n8.x4.shared.b16 [%0], {%1, %2, %3, %4};" ::"r"(a), "r"(r0), "r"(r1), "r"(r2), "r"(r3) : "memory"); }
__device__ __forceinline__ void stsm4t(uint32_t a, uint32_t r0, uint32_t r1, uint32_t r2, uint32_t r3) { asm volatile("stmatrix.sync.aligned.m8n8.x4.trans.shared.b16 [%0], {%1, %2, %3, %4};" ::"r"(a), "r"(r0), "r"(r1), "r"(r2), "r"(r3) : "memory"); }
__device__ __forceinline__ void ldsm4(uint32_t a, uint32_t* r) { asm volatile("ldmatrix.sync.aligned.m8n8.x4.shared.b16 {%0, %1, %2, %3}, [%4];" : "=r"(r[0]), "=r"(r[1]), "=r"(r[2]), "=r"(r[3]) : "r"(a) : "memory"); }
__device__ __forceinline__ void ldsm4t(uint32_t a, uint32_t* r) { asm volatile("ldmatrix.sync.aligned.m8n8.x4.trans.shared.b16 {%0, %1, %2, %3}, [%4];" : "=r"(r[0]), "=r"(r[1]), "=r"(r[2]), "=r"(r[3]) : "r"(a) : "memory"); }

__device__ __forceinline__ float swiglu(float g, float u) {
  const float hg = 0.5f * g, q = hg * u;
  float th;
  asm("tanh.approx.f32 %0, %1;" : "=f"(th) : "f"(hg));
  return fmaf(q, th, q);
}

__device__ __forceinline__ uint32_t swiglu2(float g0, float g1, float u0, float u1) {
  return pack_bf16(swiglu(g0, u0), swiglu(g1, u1));
}

struct cf { float r, i; };
__device__ __forceinline__ cf cmul(cf a, cf b) { return {a.r * b.r - a.i * b.i, a.r * b.i + a.i * b.r}; }
__device__ __forceinline__ cf csq(cf a) { return {a.r * a.r - a.i * a.i, (a.r + a.r) * a.i}; }
__device__ __forceinline__ cf cpow_seed(float a2, float beta, float p) {
  float e;
  asm("ex2.approx.ftz.f32 %0, %1;" : "=f"(e) : "f"(a2 * p));
  const float th = beta * p;
  return {e * __cosf(th), e * __sinf(th)};
}
__device__ __forceinline__ void hcmul(uint32_t r, uint32_t i, uint32_t w, uint32_t& ro, uint32_t& io) {
  const __half2 hr = *reinterpret_cast<__half2*>(&r), hi = *reinterpret_cast<__half2*>(&i), hw = *reinterpret_cast<__half2*>(&w);
  const __half2 hwr = __low2half2(hw), hwi = __high2half2(hw);
  __half2 a = __hfma2(hr, hwr, __hneg2(__hmul2(hi, hwi)));
  __half2 b = __hfma2(hr, hwi, __hmul2(hi, hwr));
  ro = *reinterpret_cast<uint32_t*>(&a);
  io = *reinterpret_cast<uint32_t*>(&b);
}

struct Modes {
  uint32_t la, ai, cr, ci;
  uint32_t e;
  float dt;
};
__device__ __forceinline__ Modes load_modes(uint32_t park, int lc, int odd_cta, int mu) {
  Modes m;
  const uint32_t a = park + 256 * lc + 4 * mu, b = park + 4224 + 8 * odd_cta + 2 * lc;
  m.la = lds32(a); m.ai = lds32(a + 1024); m.cr = lds32(a + 2048); m.ci = lds32(a + 3072);
  const uint32_t o0 = lds32((a ^ 128) + 2048), o1 = lds32((a ^ 128) + 3072), ld = lds16(b), dsk = lds16(b + 16);
  const uint32_t m2 = __vmaxu2(__vmaxu2(m.cr & 0x7fff7fffu, m.ci & 0x7fff7fffu), __vmaxu2(o0 & 0x7fff7fffu, o1 & 0x7fff7fffu));
  m.e = min(max(__reduce_max_sync(0xffffffffu, max(m2 & 0xffffu, m2 >> 16)) >> 7, 1u), 253u) << 23 | dsk;
  m.dt = bf_round(expf(bf_lo(ld)));
  return m;
}
struct Powers { uint32_t re[3][4], im[3][4]; cf z4; };
__device__ __forceinline__ void powers(const Modes& m, Powers& g) {
  const float la2 = -bf_round(expf(bf_lo(m.la))) * m.dt * 1.4426950408889634f;
  const float beta = bf_lo(m.ai) * m.dt;
  const cf z1 = cpow_seed(la2, beta, 1.f), z2 = csq(z1), z3 = cmul(z2, z1), z4 = csq(z2), z5 = cmul(z4, z1), z6 = csq(z3), z7 = cmul(z4, z3);
  g.z4 = z4;
  g.re[0][0] = pack_f16(1.f, z4.r); g.re[0][1] = pack_f16(z2.r, z6.r); g.re[0][2] = pack_f16(z1.r, z5.r); g.re[0][3] = pack_f16(z3.r, z7.r);
  g.im[0][0] = pack_f16(0.f, z4.i); g.im[0][1] = pack_f16(z2.i, z6.i); g.im[0][2] = pack_f16(z1.i, z5.i); g.im[0][3] = pack_f16(z3.i, z7.i);
  const cf v1 = cpow_seed(la2, beta, 256.f), v2 = csq(v1), v3 = cmul(v2, v1), v4 = csq(v2), v5 = cmul(v4, v1), v6 = csq(v3), v7 = cmul(v4, v3), v8 = csq(v4);
  const uint32_t p1 = pack_f16(v1.r, v1.i);
  hcmul(g.re[0][0], g.im[0][0], p1, g.re[1][0], g.im[1][0]);
  hcmul(g.re[0][1], g.im[0][1], p1, g.re[1][1], g.im[1][1]);
  hcmul(g.re[0][0], g.im[0][0], pack_f16(v2.r, v2.i), g.re[1][2], g.im[1][2]);
  hcmul(g.re[0][0], g.im[0][0], pack_f16(v3.r, v3.i), g.re[1][3], g.im[1][3]);
  g.re[2][0] = pack_f16(v4.r, v5.r); g.re[2][1] = pack_f16(v6.r, v7.r); g.re[2][2] = g.re[2][3] = pack_f16(v8.r, 0.f);
  g.im[2][0] = pack_f16(v4.i, v5.i); g.im[2][1] = pack_f16(v6.i, v7.i); g.im[2][2] = g.im[2][3] = pack_f16(v8.i, 0.f);
}
__device__ __forceinline__ void kgen_operands(const Modes& m, const Powers& g, uint32_t buf, int chi, int mu) {
  const uint32_t sa = buf + chi * 8192 + mu * 16, sbb = buf + 16384 + chi * 6144 + mu * 16;
  auto store_b = [&](int q) {
    sts128(sbb + 2048 * q, g.re[q][0], g.re[q][1], g.re[q][2], g.re[q][3]);
    sts128(sbb + 2048 * q + 1024, g.im[q][0], g.im[q][1], g.im[q][2], g.im[q][3]);
  };
  store_b(0);
  cf w8 = csq({g.z4.r, -g.z4.i}), w16 = csq(w8);
  const float psd = __uint_as_float((254u << 23) - (m.e & 0xffff0000u));
  const cf a0 = {bf_lo(m.cr) * psd, -bf_lo(m.ci) * psd};
  asm volatile("" : "+f"(w16.r), "+f"(w16.i)::"memory");
  store_b(1);
  const cf a1 = cmul(a0, w8), a2 = cmul(a0, w16), a3 = cmul(a1, w16);
  cf w32 = csq(w16), w64 = csq(w32);
  uint32_t R[4], I[4], r[4], i[4];
  R[0] = pack_f16(a0.r, a1.r); R[1] = pack_f16(a2.r, a3.r);
  I[0] = pack_f16(a0.i, a1.i); I[1] = pack_f16(a2.i, a3.i);
  asm volatile("" : "+f"(w64.r), "+f"(w64.i)::"memory");
  store_b(2);
  const cf w128 = csq(w64), w192 = cmul(w64, w128);
  const uint32_t w[4] = {pack_f16(w32.r, w32.i), pack_f16(w64.r, w64.i), pack_f16(w128.r, w128.i), pack_f16(w192.r, w192.i)};
  hcmul(R[0], I[0], w[0], R[2], I[2]); hcmul(R[1], I[1], w[0], R[3], I[3]);
  sts128(sa, R[0], R[1], R[2], R[3]); sts128(sa + 1024, I[0], I[1], I[2], I[3]);
#pragma unroll
  for (int q = 1; q < 4; q++) {
#pragma unroll
    for (int k = 0; k < 4; k++) hcmul(R[k], I[k], w[q], r[k], i[k]);
    sts128(sa + 2048 * q, r[0], r[1], r[2], r[3]); sts128(sa + 2048 * q + 1024, i[0], i[1], i[2], i[3]);
  }
  fence_async_smem();
}
__device__ __forceinline__ void kgen_mma(float (&dk)[24], uint32_t buf, int scale) {
  const uint32_t da = (buf >> 4) | (64u << 16), db = da + 1024;
  wg_fence();
#pragma unroll
  for (int k = 0; k < 8; k++) mma_kgen(dk, da + 8 * k, db + 8 * k, scale | k);
  wg_commit();
}
__device__ __forceinline__ void kgen_dump(const float (&dk)[24], float pks, float skip, uint32_t kc, uint32_t s0, int w4, int lane) {
  const int chi = w4 >> 1, g = lane >> 2, t = lane & 3, mu = 32 * (w4 & 1) + lane;
  const int i0 = 16 * (w4 & 1) + g;
  float v[12];
  if (chi) {
#pragma unroll
    for (int k = 0; k < 12; k++) asm volatile("mul.rn.f32 %0, %1, %2;" : "=f"(v[k]) : "f"(dk[12 + k]), "f"(pks));
  } else {
#pragma unroll
    for (int k = 0; k < 12; k++) v[k] = dk[k] * pks;
  }
  if (mu == 0) v[0] += skip;
  const uint32_t b = kc + 4 * (t < 2 ? 4 + 4 * i0 + t : 4 + 64 * t + 2 * i0);
  const uint32_t be = t < 2 ? 8 : 4;
  stsf(b, v[4]); stsf(b + be, v[5]); stsf(b + 16 * be, v[6]); stsf(b + 17 * be, v[7]);
  const uint32_t c = kc + 4 * (260 + 64 * t + i0);
  if (t < 2) { stsf(c, v[8]); stsf(c + 128, v[9]); stsf(c + 32, v[10]); stsf(c + 160, v[11]); }
  else if (t == 2 && i0 == 0) stsf(c, v[8]);
  else if (mu == 63) stsf(kc + 12, v[3]);
  const uint32_t a = s0 + 16 * i0 + 2 * ((t & 1) * 2 + (t >> 1));
  const uint32_t e0 = pack_bf16(v[0], v[1]), e1 = pack_bf16(v[2], v[3]);
  sts16(a, e0); sts16(a + 8, e0 >> 16); sts16(a + 128, e1); sts16(a + 136, e1 >> 16);
  sts16(a + KT_COPY + 2, e0); sts16(a + KT_COPY + 10, e0 >> 16); sts16(a + KT_COPY + 130, e1);
  if (mu != 63) sts16(a + KT_COPY + 138, e1 >> 16);
  if (mu < 14) sts128(s0 - 112 + 16 * mu + (mu < 7 ? 0 : KT_COPY - 112), 0, 0, 0, 0);
  else if (mu == 14) sts16(s0 + KT_COPY, 0);
}
template <bool LEAN> __device__ __forceinline__ void kgen_expand(uint32_t kc, uint32_t s0, int w4, int lane) {
  const int mu = 32 * (w4 & 1) + lane;
  const bool odd = w4 & 1;
  const float4 a = ldsf4(kc + 16 + 16 * lane);
  float ax = ldsf(odd ? kc + 12 : kc + 32 + 16 * lane);
  float2 q;
  float q2, r[4];
  auto load_q = [&]() { q = ldsf2(kc + 528 + 8 * mu); q2 = ldsf(kc + 536 + 8 * mu); };
  auto load_r = [&](int k) { r[2 * k] = ldsf(kc + 1040 + 256 * k + 4 * mu); r[2 * k + 1] = ldsf(kc + 1044 + 256 * k + 4 * mu); };
  if (!LEAN) { load_q(); load_r(0); load_r(1); }
  {
    const uint32_t c22 = pack_bf16(a.z, a.z);
    if (!odd) sts128(s0 + 512 + 16 * lane, pack_bf16(a.x, a.x), pack_bf16(a.y, a.z), c22, pack_bf16(a.w, ax));
    else sts128(s0 + KT_COPY + 512 + 16 * lane, pack_bf16(lane ? a.x : ax, a.x), pack_bf16(a.x, a.y), c22, pack_bf16(a.z, a.w));
  }
  if (LEAN) { load_q(); load_r(0); }
  const uint32_t sm0 = s0 + 16 * mu, sm1 = sm0 + KT_COPY;
  {
    const uint32_t c00 = pack_bf16(q.x, q.x), c11 = pack_bf16(q.y, q.y);
    sts128(sm0 + 1024, c00, pack_bf16(q.x, q.y), c11, pack_bf16(q2, q2));
    sts128(sm1 + 1024, c00, c00, c11, pack_bf16(q.y, q2));
  }
  if (LEAN) load_r(1);
#pragma unroll
  for (int k = 0; k < 2; k++) {
    const float pa = r[2 * k], pb = r[2 * k + 1], px = (lane & 1) ? pb : pa;
    const uint32_t caa = pack_bf16(pa, pa), cbb = pack_bf16(pb, pb);
    sts128(sm0 + 2048 + 1024 * k, caa, caa, pack_bf16(px, pb), cbb);
    sts128(sm1 + 2048 + 1024 * k, caa, caa, pack_bf16(pa, px), cbb);
  }
  fence_async_smem();
}

template <int I, int E> struct ConvSeq {
  static __device__ __forceinline__ void run(float (&d)[64], uint32_t a, uint32_t b) {
    constexpr int J = I >> 1, S = I & 1;
    mma_conv<128 - 8 * J>(d, a + S * (KT_COPY / 16) + 16 * J, b + S * (UT_PAR / 16) + 8 * J, I != 0);
    ConvSeq<I + 1, E>::run(d, a, b);
  }
};
template <int E> struct ConvSeq<E, E> { static __device__ __forceinline__ void run(float (&)[64], uint32_t, uint32_t) {} };

struct Params {
  const __nv_bfloat16 *x, *w_gate, *w_up, *log_a, *a_im, *c_re, *c_im, *log_dt, *d_skip, *gate_w, *w_down;
};

__device__ __forceinline__ void extra_cta(const Params& p, const CUtensorMap* tm_x) {
  constexpr uint32_t sd = 1024, WGRP = 8208, OFF_X = 74752, B_F = OFF_BAR, B_W = OFF_BAR + 128;
  const uint32_t sb = sd + ((blockIdx.x & 1) << 24);
  const int warp = __shfl_sync(0xffffffffu, threadIdx.x >> 5, 0), lane = threadIdx.x & 31, wg = warp >> 2;
  const int row0 = 512 * (blockIdx.x - 128);
  auto x_load = [&](int ks) {
    const uint32_t bar = sb + B_F + 32 * wg + 8 * (ks & 3);
    mbar_expect(bar, 8192);
    tma2d(sb + OFF_X + 32768 * wg + 8192 * (ks & 3), tm_x, bar, 32 * ks, row0 + 128 * wg);
  };
  const int k = threadIdx.x, ng = k & 7;
  const uint8_t* wsrc = (const uint8_t*)(ng < 4 ? p.w_gate : p.w_up) + (k >> 3) * (kF * 2) + 2688 + 16 * (ng & 3);
  auto w_load = [&](int q) {
    if (q < 8) cp_async16(sb + ng * WGRP + (64 * q + (k >> 3)) * 16, wsrc + q * (64 * kF * 2));
    asm volatile("cp.async.commit_group;" ::: "memory");
  };
  const uint32_t gw = __ldg((const uint16_t*)p.gate_w + k);
  w_load(0);
  w_load(1);
  if (!(k & 127)) {
#pragma unroll
    for (int i = 0; i < 4; i++) mbar_init(sb + B_F + 32 * wg + 8 * i, 1);
    mbar_init(sb + B_W + 16 * wg, 16); mbar_init(sb + B_W + 16 * wg + 8, 16);
    fence_async_smem();
#pragma unroll 1
    for (int ks = 0; ks < 3; ks++) x_load(ks);
  }
  sts128(sb + 8 * WGRP + 16 * k, gw, 0, 0, 0);
  asm volatile("cp.async.wait_group 1;" ::: "memory");
  fence_async_smem();
  __syncthreads();
  w_load(2);
  float d0[36], d1[36];
#pragma unroll 1
  for (int ks = 0; ks < 16; ks++) {
    if (!(ks & 1) && ks) mbar_wait(sb + B_W + 4 * ks, 0);
    mbar_wait(sb + B_F + 32 * wg + 8 * (ks & 3), (ks >> 2) & 1);
    const uint32_t da = ((sd + OFF_X + 32768 * wg + 8192 * (ks & 3)) >> 4) | (1u << 16), db = ((sd >> 4) + 32 * ks) | (8u << 16);
    wg_fence();
    mma_x(d0, da, db, ks);
    mma_x(d1, da + 256, db, ks);
    mma_x(d0, da + 2, db + 16, 1);
    mma_x(d1, da + 258, db + 16, 1);
    wg_commit();
    if (!(ks & 1) && ks < 14) {
      asm volatile("cp.async.wait_group 1;" ::: "memory");
      fence_async_smem();
      __syncwarp();
      if (lane == 0) mbar_arrive(sb + B_W + 4 * ks + 8);
      w_load(ks / 2 + 3);
    }
    wg_wait<1>();
    nb_sync(1 + wg, 128);
    if (!(k & 127) && ks < 13) x_load(ks + 3);
    __syncwarp();
  }
  wg_wait<0>();
  pin(d0); pin(d1);
  uint8_t* hp = g_h + ((size_t)(row0 / 64 + 2 * (warp >> 2)) * 88 + 84) * 2048 + (warp & 3) * 256 + lane * 4;
#pragma unroll
  for (int e = 0; e < 8; e++) {
    *(uint32_t*)(hp + (e >> 1) * 1024 + (e & 1) * 128) = pack_bf16(swiglu(d0[2 * e], d0[16 + 2 * e]), swiglu(d0[2 * e + 1], d0[17 + 2 * e]));
    *(uint32_t*)(hp + 88 * 2048 + (e >> 1) * 1024 + (e & 1) * 128) = pack_bf16(swiglu(d1[2 * e], d1[16 + 2 * e]), swiglu(d1[2 * e + 1], d1[17 + 2 * e]));
  }
  {
    const float l0 = __shfl_sync(0xffffffffu, d0[32], lane & 28), l1 = __shfl_sync(0xffffffffu, d0[34], lane & 28);
    const float l2 = __shfl_sync(0xffffffffu, d1[32], lane & 28), l3 = __shfl_sync(0xffffffffu, d1[34], lane & 28);
    const float lg = (lane & 2) ? ((lane & 1) ? l3 : l2) : ((lane & 1) ? l1 : l0);
    const float gt = bf_round(1.f / (1.f + expf(-bf_round(lg))));
    g_gate[row0 + 128 * (warp >> 2) + 32 * (lane & 2) + 16 * (warp & 3) + 8 * (lane & 1) + (lane >> 2)] = pack_bf16(gt, 1.f - gt);
  }
  __syncthreads();
  if (warp == 0) {
    fence_async_all();
    if (lane < 8) asm volatile("red.relaxed.gpu.global.add.u32 [%0], 8;" ::"l"(g_flags + (FL_H + row0 / 64 + lane) * FLAG_STRIDE) : "memory");
  }
}

}

__global__ void __cluster_dims__(2, 1, 1) __launch_bounds__(512, 1)
gated_mix_kernel(const __grid_constant__ Params p, const __grid_constant__ CUtensorMap tm_x, const __grid_constant__ CUtensorMap tm_wg,
                 const __grid_constant__ CUtensorMap tm_wg3, const __grid_constant__ CUtensorMap tm_wu,
                 const __grid_constant__ CUtensorMap tm_wu3, const __grid_constant__ CUtensorMap tm_wd,
                 const __grid_constant__ CUtensorMap tm_out, const __grid_constant__ CUtensorMap tm_u,
                 const __grid_constant__ CUtensorMap tm_xp, const __grid_constant__ CUtensorMap tm_ul) {
  extern __shared__ uint8_t smem_raw[];
  constexpr uint32_t sd = 1024;
  if (blockIdx.x >= 128) { extra_cta(p, &tm_x); return; }
  const int rank = blockIdx.x & 1, cl = blockIdx.x >> 1;
  const uint32_t sb = sd + ((uint32_t)rank << 24);
  {
    const uint32_t k = threadIdx.x & 15, kind = (threadIdx.x >> 4) & 3, share = (blockIdx.x * 2 + (threadIdx.x >> 6)) & 127;
    const uint8_t* base = (const uint8_t*)(kind == 0 ? p.x : kind == 1 ? p.w_gate : p.w_up);
    const uint32_t off = kind == 0 ? (16 * share + k) * 1024 : (11 * share + k) * 128;
    if (threadIdx.x < 64 * 2 && kind < 3 && (kind == 0 || k < 11)) asm volatile("prefetch.global.L2 [%0];" ::"l"(base + off) : "memory");
  }
  if (threadIdx.x == 384) {
    asm volatile("prefetch.tensormap [%0];" ::"l"(&tm_wg + 2 * rank) : "memory");
    asm volatile("prefetch.tensormap [%0];" ::"l"(&tm_wg3 + 2 * rank) : "memory");
    asm volatile("prefetch.tensormap [%0];" ::"l"(&tm_x) : "memory");
    init_barriers<0, 12>(sb + OFF_BAR);
    asm volatile("fence.mbarrier_init.release.cluster;" ::: "memory");
    fence_async_smem();
  }
  __syncwarp();
  asm volatile("barrier.cluster.arrive.relaxed.aligned;" ::: "memory");
  const int warp = __shfl_sync(0xffffffffu, threadIdx.x >> 5, 0);
  const int lane = threadIdx.x & 31;
  const int wg = warp >> 2, w4 = warp & 3;
  const int row7 = ((cl - 36) * 37) >> 8;
  const int ia = 8 + 2 * cl, ib = 16 * ((cl - 4) & 7) + 2 * ((cl - 4) >> 3), ic = 16 * cl - 552 - 110 * row7;
  const int cta = rank + selp(ia, selp(ib, ic, cl < 36), cl < 4);
  const int mb = 2 * (cta >> 4) + rank;
  const int nb = (cta >> 1) & 7;
  const int m2 = cta >> 3;
  const int tb = 2 * m2 + rank;
  const int cq = (cta >> 1) & 3;

  auto g1_load = [&](int ks, uint32_t slot) {
    const uint32_t bar = sb + B_FULL1 + 8 * slot, dst = sb + slot * SLOT1;
    mbar_expect(bar, 8192 + 2 * (8192 + 2560));
    tma3d_pair(dst + 8192 + 12288 * rank, &tm_wg + 2 * rank, bar, 64 * nb, 32 * ks, 0);
    tma2d_pair(dst + 16384 + 12288 * rank, &tm_wg3 + 2 * rank, bar, 1024 + 40 * nb, 32 * ks);
    tma2d(dst, &tm_x, bar, 32 * ks, 128 * mb);
  };

  if (wg == 2) {
    asm volatile("setmaxnreg.dec.sync.aligned.u32 88;");
    const int tau = threadIdx.x & 127, chi = w4 >> 1, mu = tau & 63;

    const uint32_t kc = sb + OFF_PARK + chi * KC_CH;
    {
      const int o = 1024 * cta + 16 * mu;
      cp_async16(sb + OFF_PARK + 16 * tau, (const uint8_t*)(w4 < 2 ? p.log_a : p.a_im) + o);
      cp_async16(sb + OFF_PARK + 2048 + 16 * tau, (const uint8_t*)(w4 < 2 ? p.c_re : p.c_im) + o);
      if (!(tau & 63)) cp_async16(sb + OFF_PARK + 4224 + 8 * w4, (const uint8_t*)(w4 ? p.d_skip : p.log_dt) + 16 * (cta >> 1));
    }
    asm volatile("cp.async.wait_all;" ::: "memory");
    nb_sync(NB_PAR, 224);
    Modes m = load_modes(sb + OFF_PARK, conv_ch(chi), cta & 1, mu);
    Powers pw;
    powers(m, pw);
    float dk[24];
#pragma unroll 1
    for (int it = 0; it < 4; it++) {
      kgen_operands(m, pw, sb + OFF_KS, chi, mu);
      nb_sync(NB_AUX, 128);
      int tid_local = threadIdx.x;
      asm volatile("" : "+r"(tid_local), "+r"(m.e));
      const int lane = tid_local & 31, mu = tid_local & 63;
      kgen_mma(dk, sd + OFF_KS, it & 1);
      float pks = 2.f * m.dt * bf_hi(m.e), skip = bf_lo(m.e);
      asm volatile("" : "+f"(pks), "+f"(skip));
      if (it == 1) {
        m = load_modes(sb + OFF_PARK, conv_ch(2 + chi), cta & 1, mu);
      } else {
        m.la >>= 16; m.ai >>= 16; m.cr >>= 16; m.ci >>= 16;
      }
      if (it < 3) powers(m, pw);
      wg_wait<0>();
      pin(dk);
      nb_sync(NB_AUX, 128);
      if (it & 1) mbar_wait(sb + (it == 1 ? B_XTREAD : B_TAB), 0);
      if (it & 1) kgen_dump(dk, pks, skip, kc, sb + (it == 1 ? OFF_A : OFF_KT23) + chi * KT_CH + 112, w4, lane);
      if (it == 1) { fence_async_smem(); nb_arrive(NB_KC0, 192); }
    }
    nb_sync(NB_AUX, 128);
    kgen_expand<false>(kc, sb + OFF_KT23 + chi * KT_CH + 112, w4, lane);
    __syncwarp();
    if (lane == 0) mbar_arrive(sb + B_TAB + 8);

    {
      const int half = lane >> 4, wd = 16 * (w4 & 1) + (lane & 15), row0 = 16 * (w4 >> 1) + half;
      uint32_t pa[4];
#pragma unroll
      for (int r = 0; r < 4; r++) {
        const int sw = (wd - r) & 31, row = row0 - (wd < r);
        pa[r] = sb + OFF_P + r * 4096 + row * 128 + 16 * ((sw >> 2) ^ r ^ (4 * (row & 1))) + 4 * (sw & 3);
      }
#pragma unroll 1
      for (int c = 0; c < 4; c++) {
        const int ch = 4 * cta + conv_ch(c);
        uint8_t* yo = g_y + ((size_t)row0 * 512 + ch) * 128 + 16 * ((wd >> 2) ^ (ch & 7)) + 4 * (wd & 3);
        nb_sync(NB_PFULL0 + (c & 1), 256);
        uint32_t o[8];
        const uint32_t pb = (c & 1) ? 0 : OFF_RECV;
#pragma unroll
        for (int k = 0; k < 8; k++) {
          uint32_t v0 = lds32(pa[0] + pb + 256 * k), v1 = lds32(pa[1] + pb + 256 * k), v2 = lds32(pa[2] + pb + 256 * k), v3 = lds32(pa[3] + pb + 256 * k);
          if (k == 0 && row0 == 0) { if (wd < 1) v1 = 0; if (wd < 2) v2 = 0; if (wd < 3) v3 = 0; }
          o[k] = badd2(badd2(v0, v1), badd2(v2, v3));
        }
#pragma unroll
        for (int k = 0; k < 8; k++) *(uint32_t*)(yo + (size_t)k * 131072) = o[k];
        __syncwarp();
        if (lane == 0) mbar_arrive(sb + B_PEMPTY + 8 * c);
      }
      nb_sync(NB_AUX, 128);
      if (tau == 0) flag_signal(FL_Y + (cta >> 5), 1);
      __syncwarp();
    }
    if (lane == 0) mbar_arrive(sb + B_DONE);
    return;
  }

  if (warp == 12) {
    cluster_wait();
    if (elect()) {
      g1_load(0, 0);
    }
    __syncwarp();
  }

  if (wg == 1 && w4 < 3) {
    if (elect()) {
      if (w4 == 0) init_barriers<12, 26>(sb + OFF_BAR);
      else if (w4 == 1) init_barriers<26, 40>(sb + OFF_BAR);
      else init_barriers<40, 55>(sb + OFF_BAR);
      fence_async_smem();
    }
    __syncwarp();
    nb_arrive(NB_INIT, 192);
    nb_arrive(NB_PAR, 224);
  }

  if (wg == 3) {
    asm volatile("setmaxnreg.dec.sync.aligned.u32 24;");
    if (w4) { cluster_wait(); nb_sync(NB_INIT, 192); }
    auto h_publish = [&](int w) {
      uint32_t* f = g_flags + (FL_H + 2 * mb + w) * FLAG_STRIDE;
      asm volatile("" : "+l"(f));
      nb_sync(NB_H0 + w, 160);
      if (elect()) {
        asm volatile("red.release.gpu.global.add.u32 [%0], 3;" ::"l"(f) : "memory");
      }
      __syncwarp();
    };
    const uint8_t* hsrc = g_h + ((size_t)2 * m2 * 88 + 43 * rank) * 2048;
    if (w4 >= 2) {
      const int ii = lane & 7;
      const uint32_t src = sb + OFF_A + (64 * (w4 & 1) + 7 - ii) * 128 + 16 * ((lane >> 3) ^ (7 - ii));
      const uint32_t dst = sb + OFF_UT + lane * 128 + 16 * ((4 * (1 - (w4 & 1))) ^ ii);
      mbar_wait(sb + B_XTFULL, 0);
#pragma unroll 1
      for (int r = 0; r < 8; r++) {
        uint32_t v[8];
        ldsm4(src + r * 1024, v);
        ldsm4((src + r * 1024) ^ 64, v + 4);
        const uint32_t o = (dst + (r & 1) * 8192) ^ (8 * (r & 6));
        stsm4t(o, v[0], v[1], v[2], v[3]);
        stsm4t(o + 4096, v[4], v[5], v[6], v[7]);
      }
      fence_async_smem();
      nb_arrive(NB_UT, 96);
      nb_sync(NB_KC0, 192);
#pragma unroll 1
      for (int half = 0; half < 2; half++) {
        kgen_expand<true>(sb + OFF_PARK + (w4 & 1) * KC_CH, sb + OFF_A + (w4 & 1) * KT_CH + 112, half, lane);
        __syncwarp();
        if (lane == 0) mbar_arrive(sb + B_TAB);
      }
    }
    if (w4 == 0) {
      if ((uint32_t)__cvta_generic_to_shared(smem_raw) != sb) __trap();
      uint32_t slot = 1, ph = 1;
#pragma unroll 1
      for (int ks = 1; ks < 16; ks++) {
        mbar_wait(sb + B_EMPTY1 + 8 * slot, ph);
        if (elect()) g1_load(ks, slot);
        __syncwarp();
        if (++slot == 5) { slot = 0; ph ^= 1; }
      }
      if (elect()) mbar_expect(sb + B_WF, 5 * 16384);
#pragma unroll 1
      for (int q = 0; q < 11; q++) {
        const int st = q < 4 ? q + 1 : q == 4 ? 0 : q;
        slot = st < 6 ? st : st - 6;
        mbar_wait(sb + (q < 4 ? B_EMPTY1 + 8 + 8 * (q >> 1) : q == 4 ? B_G1DONE : q == 5 ? B_PEMPTY + 16 : B_EMPTYW + 8 * slot), 0);
        if (elect()) {
          const uint32_t bar = sb + (st < 5 ? B_WF : st == 5 ? B_W5 : B_FULL3 + 8 * slot);
          if (st >= 5) mbar_expect(bar, 16384);
          tma3d(sb + OFF_W2 + 16384 * slot, &tm_wd, bar, 0, 688 * rank + 64 * st, 2 * cq);
          if (st >= 6) bulk_load(sb + OFF_A + 8192 * slot, hsrc + rank * (88 * 2048) + st * 8192, st == 10 ? 6144 : 8192, sb + B_KH);
        }
        __syncwarp();
      }
    } else if (w4 == 1) {
      uint32_t target;
      asm volatile("ld.relaxed.gpu.global.u32 %0, [%1];" : "=r"(target) : "l"(g_flags + (FL_U + nb) * FLAG_STRIDE) : "memory");
      target = (target & ~31u) + 32;
      if (elect()) {
        sts32(sb + OFF_EPOCH, target);
        mbar_expect(sb + B_XTFULL, 16384);
        tma4d(sb + OFF_A, &tm_xp, sb + B_XTFULL, 64 * nb, 0, 0, 2 * mb);
#pragma unroll
        for (int i = 0; i < 5; i++) if (i != 3) asm volatile("prefetch.tensormap [%0];" ::"l"(&tm_wd + i) : "memory");
      }
      __syncwarp();
      nb_sync(NB_UT, 96);
      if (elect()) {
        mbar_arrive(sb + B_XTREAD);
        tma3d_store(&tm_u, sb + OFF_UT, 32 * (30 - 2 * mb), 64 * nb, 0);
        asm volatile("cp.async.bulk.commit_group;" ::: "memory");
        asm volatile("cp.async.bulk.wait_group 0;" ::: "memory");
      }
      __syncwarp();
      if (elect()) {
        flag_signal(FL_U + nb, 2);
        asm volatile("cp.async.bulk.prefetch.L2.global [%0], %1;" ::"l"((const uint8_t*)p.w_down + (size_t)cta * 11008), "r"(11008) : "memory");
        mbar_expect(sb + B_UFULL, 4 * UT_CH);
        flag_wait(FL_U + (cta >> 4), target);
        tma4d(sb + OFF_UT, &tm_ul, sb + B_UFULL, 0, 0, 0, 4 * cta);
        mbar_expect(sb + B_RECV, 16384);
      }
      __syncwarp();
      mbar_wait(sb + B_G1DONE, 0);
      if (elect()) {
#pragma unroll 1
        for (int s = 0; s < 6; s++) mbar_expect(sb + B_HE + 8 * s, 8192);
        flag_wait(FL_H + 2 * m2, target);
#pragma unroll
        for (int s = 0; s < 6; s++) bulk_load(sb + OFF_HE + 8192 * s, hsrc + s * 8192, 8192, sb + B_HE + 8 * s);
        if (rank == 0) flag_wait(FL_H + 2 * m2 + 1, target);
#pragma unroll 1
        for (int s = 0; s < 5; s++) {
          const uint32_t bytes = s == 4 ? 6144 : 8192;
          mbar_expect(sb + B_FULL3 + 8 * s, bytes);
          mbar_wait(sb + B_EMPTYH + 8 * s, 0);
          bulk_load(sb + OFF_HE + 8192 * s, hsrc + (rank ^ 1) * (88 * 2048) + 49152 + s * 8192, bytes, sb + B_FULL3 + 8 * s);
        }
      }
      __syncwarp();
    } else if (w4 == 2) {
      h_publish(0);
      mbar_wait(sb + B_PEMPTY + 24, 0);
      if (elect()) {
        mbar_expect(sb + B_YFULL, 16384);
        flag_wait(FL_Y + cq, lds32(sb + OFF_EPOCH));
        bulk_load(sb + OFF_P, g_y + ((size_t)tb * 512 + 128 * cq) * 128, 16384, sb + B_YFULL);
      }
      __syncwarp();
    } else {
      if (elect()) {
#pragma unroll 1
        for (int s = 0; s < 6; s++) mbar_expect(sb + B_HL + 8 * s, 8192);
        mbar_expect(sb + B_KH, 38912 + 256);
      }
      __syncwarp();
      const uint32_t target = lds32(sb + OFF_EPOCH);
      h_publish(1);
      if (elect()) {
        flag_wait(FL_H + 2 * m2 + 1, target);
        mbar_wait(sb + B_C12, 0);
#pragma unroll
        for (int s = 0; s < 6; s++) bulk_load(sb + (s < 5 ? OFF_A + 8192 * s : OFF_HL5), hsrc + 88 * 2048 + s * 8192, 8192, sb + B_HL + 8 * s);
        bulk_load(sb + OFF_GATE, g_gate + 64 * tb, 256, sb + B_KH);
      }
      __syncwarp();
      mbar_wait(sb + B_DONE, 0);
      return;
    }
    if (lane == 0) mbar_arrive(sb + B_DONE);
  } else {
    nb_sync(NB_SKEW, 256);
    asm volatile("setmaxnreg.inc.sync.aligned.u32 200;");
    cluster_wait();
    {
      float ag[84], au[84];
      const uint32_t da0 = ((sd >> 4) + wg * 256) | (1u << 16);
      constexpr uint32_t db0 = ((sd >> 4) + 512) | (256u << 16);
      const uint32_t rel = sd + B_EMPTY1 + (lane << 24);
      auto release = [&](int slot) { if (lane < 2) mbar_arrive_cluster(rel + 8 * slot); };
      auto g1_stage = [&](int slot, uint32_t ph, int scale) {
        mbar_wait(sb + B_FULL1 + 8 * slot, ph);
        const uint32_t da = da0 + slot * (SLOT1 / 16), db = db0 + slot * (SLOT1 / 16);
        wg_fence();
        mma_g1(ag, da, db, scale);
        mma_g1(au, da, db + 768, scale);
        wg_commit();
        mma_g1(ag, da + 2, db + 128, 1);
        mma_g1(au, da + 2, db + 768 + 128, 1);
        wg_commit();
      };
#pragma unroll 1
      for (int it = 0; it < 2; it++) {
#pragma unroll
        for (int q = 0; q < 5; q++) {
          g1_stage(q, it, it | q);
          wg_wait<2>();
          if (q || it) release((q + 4) % 5);
          wg_wait<1>();
        }
      }
#pragma unroll
      for (int q = 0; q < 6; q++) {
        if (q == kSkewAt && wg == 1) { wg_wait<0>(); release(q - 1); nb_sync(NB_SKEW, 256); }
        g1_stage(q % 5, q / 5, 1);
        if (q == 5) nb_arrive(wg ? NB_GO0 : NB_SKEW, 256);
        if (q < 5) {
          wg_wait<2>();
          if (!(q == kSkewAt && wg == 1)) release((q + 4) % 5);
          if (q < kSkewAt - 1) wg_wait<1>();
        }
      }
      wg_wait<0>();
      pin(ag); pin(au);
      if (lane == 0) mbar_arrive(sb + B_G1DONE);
      uint8_t* hp = g_h + (size_t)(2 * mb + wg) * 88 * 2048 + nb * 8192 + w4 * 256 + lane * 4;
#pragma unroll
      for (int j = 0; j < 21; j++) {
        if (j == 16) hp -= nb * 3072;
#pragma unroll
        for (int e = 0; e < 2; e++)
          *(uint32_t*)(hp + (j >> 3) * 65536 + (j & 7) * 1024 + e * 128) =
              swiglu2(ag[4 * j + 2 * e], ag[4 * j + 2 * e + 1], au[4 * j + 2 * e], au[4 * j + 2 * e + 1]);
        if (j == 6) sched_fence(gridDim.x, j);
        if (j == 13) { mbar_wait(sb + B_TAB, 0); mbar_wait(sb + B_UFULL, 0); }
      }
      nb_arrive(NB_H0 + wg, 160);
    }
    const int mat = lane >> 3, ii = lane & 7;
    {
      uint32_t pw = sb + (wg ? OFF_P : OFF_RECV) + (ii & 3) * 4096 + (31 - 2 * (mat >> 1) - (ii >> 2)) * 128 +
                    16 * ((2 * w4 + (mat & 1)) ^ (ii & 3) ^ (4 * (1 - (ii >> 2))));
      uint32_t da = ((sd + OFF_A + wg * KT_CH) >> 4) | (8u << 16), db = ((sd + OFF_UT + conv_ch(wg) * UT_CH) >> 4) | (4u << 16);
#pragma unroll 1
      for (int r = 0; r < 2; r++) {
        nb_sync(NB_GO0 + wg, 256);
        float d[64];
        wg_fence();
        ConvSeq<0, kConvHead>::run(d, da, db);
        nb_sync_if(r | wg, NB_ST0 + wg, 256);
        ConvSeq<kConvHead, 32>::run(d, da, db);
        wg_commit();
        nb_arrive(NB_GO0 + (wg ^ 1), 256);
        mbar_wait(sb + (r ? B_PEMPTY + 8 * wg : B_G1DONE), 0);
        wg_wait<0>();
        pin(d);
        if (r != wg && lane == 0) mbar_arrive(sb + B_C12);
#pragma unroll
        for (int q = 0; q < 8; q++)
          stsm4t(pw - 512 * q, pack_bf16(d[8 * q], d[8 * q + 1]), pack_bf16(d[8 * q + 2], d[8 * q + 3]),
                 pack_bf16(d[8 * q + 4], d[8 * q + 5]), pack_bf16(d[8 * q + 6], d[8 * q + 7]));
        nb_arrive(NB_PFULL0 + wg, 256);
        nb_arrive(NB_ST0 + (wg ^ 1), 256);
        if (!r) mbar_wait(sb + B_TAB + 8, 0);
        da += (OFF_KT23 - OFF_A) / 16;
        db += wg ? -(int)(2 * UT_CH / 16) : (int)(2 * UT_CH / 16);
      }
    }
    const bool keeper = wg == rank;
    const uint32_t peer = sb ^ (1u << 24);
    float d[64];
    auto g2_stage = [&](uint32_t da, int slot, int nk, int scale) {
      const uint32_t db = ((sd + OFF_W2 + 16384 * slot) >> 4) | (512u << 16);
      wg_fence();
#pragma unroll
      for (int k = 0; k < nk; k++) {
        mma_g2(d, da + 128 * k, db + 128 * k, scale | k);
        if (!scale && k == kG2Head - 1) nb_sync_if(wg == 0, NB_ST0, 256);
      }
      wg_commit();
    };
    constexpr uint32_t dae = ((sd + OFF_HE) >> 4) | (64u << 16), dal = ((sd + OFF_A) >> 4) | (64u << 16);
    {
      const uint32_t da = wg ? dal : dae, da5 = wg ? ((sd + OFF_HL5) >> 4) | (64u << 16) : dae + 5 * 512;
      mbar_wait(sb + B_WF, 0);
      mbar_wait(sb + B_HE - 48 * wg, 0);
      if (wg == 0) nb_sync(NB_GO0, 256);
#pragma unroll
      for (int st = 0; st < 6; st++) {
        g2_stage(st < 5 ? da + 512 * st : da5, st, 4, st);
        if (st < 5) mbar_wait(sb + B_HE - 48 * wg + 8 * (st + 1), 0);
        if (st == 4) mbar_wait(sb + B_W5, 0);
        if (st > 0) {
          wg_wait<1>();
          if (lane == 0) { if (!wg) mbar_arrive(sb + B_EMPTYH + 8 * (st - 1)); mbar_arrive(sb + B_EMPTYW + 8 * (st - 1)); }
        }
      }
    }
    auto send_ok = [&]() { if (lane == 0) asm volatile("mbarrier.arrive.shared::cluster.b64 _, [%0];" ::"r"(peer + B_SENDOK) : "memory"); };
    if (!keeper) {
#pragma unroll
      for (int s = 0; s < 5; s++) {
        mbar_wait(sb + B_FULL3 + 8 * s, 0);
        g2_stage(dae + 512 * s, s, s < 4 ? 4 : 3, 1);
        if (s == 0) { wg_wait<1>(); send_ok(); }
      }
      nb_arrive(NB_SENT, 256);
      if (lane == 0) mbar_arrive(sb + B_DONE);
      mbar_wait(sb + B_SENDOK, 0);
      wg_wait<0>();
      pin(d);
      const uint32_t dst = peer + OFF_RECV + w4 * 4096 + lane * 16;
#pragma unroll
      for (int jj = 0; jj < 8; jj++)
        asm volatile("st.async.shared::cluster.mbarrier::complete_tx::bytes.v4.b32 [%0], {%1, %2, %3, %4}, [%5];"
                     ::"r"(dst + jj * 512), "r"(pack_bf16(d[8 * jj], d[8 * jj + 1])), "r"(pack_bf16(d[8 * jj + 2], d[8 * jj + 3])),
                       "r"(pack_bf16(d[8 * jj + 4], d[8 * jj + 5])), "r"(pack_bf16(d[8 * jj + 6], d[8 * jj + 7])), "r"(peer + B_RECV) : "memory");
    } else {
      wg_wait<0>();
      send_ok();
      mbar_wait(sb + B_KH, 0);
      const uint32_t ya = sb + OFF_P + (8 * (mat >> 1) + ii) * 128 + 16 * ((2 * w4 + (mat & 1)) ^ ii);
      const uint32_t ra = sb + OFF_RECV + w4 * 4096 + lane * 16;
      const uint32_t oa = sb + OFF_RECV + w4 * 4096 + (ii + 8 * (mat & 1)) * 128;
      const uint32_t ga = lds32(sb + OFF_GATE + 4 * (16 * w4 + (lane >> 2))), gb = lds32(sb + OFF_GATE + 4 * (16 * w4 + (lane >> 2)) + 32);
      const uint32_t g0 = __byte_perm(ga, 0, 0x1010), g1 = __byte_perm(gb, 0, 0x1010);
      const uint32_t o0 = __byte_perm(ga, 0, 0x3232), o1 = __byte_perm(gb, 0, 0x3232);
      nb_sync(NB_SENT, 256);
#pragma unroll
      for (int s = 0; s < 5; s++) g2_stage(dal + 512 * s, s, s < 4 ? 4 : 3, 1);
      if (lane == 0) mbar_arrive(sb + B_DONE);
      uint32_t yv[32];
      float4 rv[8];
      mbar_wait(sb + B_YFULL, 0);
#pragma unroll
      for (int jj = 0; jj < 4; jj++) ldsm4t(ya + jj * 2048, yv + 4 * jj);
      mbar_wait(sb + B_RECV, 0);
#pragma unroll
      for (int jj = 0; jj < 8; jj++) {
        rv[jj] = ldsf4(ra + jj * 512);
        if (jj >= 4) ldsm4t(ya + jj * 2048, yv + 4 * jj);
      }
      wg_wait<0>();
      pin(d);
#pragma unroll
      for (int jj = 0; jj < 8; jj++) {
        const uint32_t r[4] = {__float_as_uint(rv[jj].x), __float_as_uint(rv[jj].y), __float_as_uint(rv[jj].z), __float_as_uint(rv[jj].w)};
#pragma unroll
        for (int e = 0; e < 4; e++) {
          const uint32_t o = (e & 1) ? o1 : o0;
          yv[4 * jj + e] = bfma2((e & 1) ? g1 : g0, yv[4 * jj + e], bmul2(o, badd2(r[e], pack_bf16(d[8 * jj + 2 * e], d[8 * jj + 2 * e + 1]))));
        }
        stsm4(oa + (jj >> 2) * 2048 + 16 * ((2 * (jj & 3) + (mat >> 1)) ^ ii), yv[4 * jj], yv[4 * jj + 1], yv[4 * jj + 2], yv[4 * jj + 3]);
        if ((jj & 3) == 3) {
          fence_async_smem();
          __syncwarp();
          if (elect()) tma3d_store(&tm_out, sb + OFF_RECV + w4 * 4096 + (jj >> 2) * 2048, 0, 64 * tb + 16 * w4, 2 * cq + (jj >> 2));
        }
      }
      if (elect()) {
        asm volatile("cp.async.bulk.commit_group;" ::: "memory");
        asm volatile("cp.async.bulk.wait_group.read 0;" ::: "memory");
      }
      __syncwarp();
    }
  }
}

typedef CUresult (*EncodeFn)(CUtensorMap*, CUtensorMapDataType, cuuint32_t, void*, const cuuint64_t*, const cuuint64_t*,
                             const cuuint32_t*, const cuuint32_t*, CUtensorMapInterleave, CUtensorMapSwizzle,
                             CUtensorMapL2promotion, CUtensorMapFloatOOBfill);

static void encode(EncodeFn fn, CUtensorMap* m, const void* base, int rank, const cuuint64_t* dims, const cuuint64_t* strides,
                   const cuuint32_t* box, CUtensorMapSwizzle sw) {
  const cuuint32_t es[4] = {1, 1, 1, 1};
  fn(m, CU_TENSOR_MAP_DATA_TYPE_BFLOAT16, rank, const_cast<void*>(base), dims, strides, box, es, CU_TENSOR_MAP_INTERLEAVE_NONE, sw,
     CU_TENSOR_MAP_L2_PROMOTION_L2_128B, CU_TENSOR_MAP_FLOAT_OOB_FILL_NONE);
}

extern "C" void kernel_launch(void* const* d_in, const int* in_sizes, int n_in, void* d_out, int out_size) {
  void* fp = nullptr;
  cudaDriverEntryPointQueryResult qr;
  cudaGetDriverEntryPoint("cuTensorMapEncodeTiled", &fp, cudaEnableDefault, &qr);
  EncodeFn fn = (EncodeFn)fp;
  CUtensorMap tm_x, tm_wg, tm_wg3, tm_wu, tm_wu3, tm_wd, tm_out, tm_u, tm_xp, tm_ul;
  {
    const cuuint64_t dims[2] = {kD, kL}, st[1] = {kD * 2};
    const cuuint32_t box[2] = {32, 128};
    encode(fn, &tm_x, d_in[0], 2, dims, st, box, CU_TENSOR_MAP_SWIZZLE_64B);
  }
  {
    const cuuint64_t dims[3] = {512, kD, 2}, dim3[2] = {kF, kD}, st[2] = {kF * 2, 1024};
    const cuuint32_t box[3] = {64, 32, 2}, box3[2] = {40, 32};
    encode(fn, &tm_wg, d_in[8], 3, dims, st, box, CU_TENSOR_MAP_SWIZZLE_128B);
    encode(fn, &tm_wu, d_in[9], 3, dims, st, box, CU_TENSOR_MAP_SWIZZLE_128B);
    encode(fn, &tm_wg3, d_in[8], 2, dim3, st, box3, CU_TENSOR_MAP_SWIZZLE_128B);
    encode(fn, &tm_wu3, d_in[9], 2, dim3, st, box3, CU_TENSOR_MAP_SWIZZLE_128B);
  }
  {
    const cuuint64_t st[2] = {kD * 2, 128};
    const cuuint32_t box[3] = {64, 64, 2};
    const cuuint64_t dw[3] = {64, kF, 8}, dx[3] = {64, kL, 8};
    encode(fn, &tm_wd, d_in[10], 3, dw, st, box, CU_TENSOR_MAP_SWIZZLE_128B);
    const cuuint32_t boxo[3] = {64, 16, 1};
    encode(fn, &tm_out, d_out, 3, dx, st, boxo, CU_TENSOR_MAP_SWIZZLE_128B);
  }
  {
    void* u = nullptr;
    cudaGetSymbolAddress(&u, g_u);
    const cuuint64_t dims[3] = {1024, 512, 2}, st[2] = {2048, 512 * 2048};
    const cuuint32_t box[3] = {64, 64, 2};
    encode(fn, &tm_u, u, 3, dims, st, box, CU_TENSOR_MAP_SWIZZLE_128B);
    const cuuint64_t diml[4] = {64, 16, 2, 512}, stl[3] = {128, 512 * 2048, 2048};
    const cuuint32_t boxl[4] = {64, 17, 2, 4};
    encode(fn, &tm_ul, u, 4, diml, stl, boxl, CU_TENSOR_MAP_SWIZZLE_NONE);
  }
  {
    const cuuint64_t dims[4] = {kD, 8, 8, 32}, st[3] = {8 * kD * 2, kD * 2, 64 * kD * 2};
    const cuuint32_t box[4] = {64, 8, 8, 2};
    encode(fn, &tm_xp, d_in[0], 4, dims, st, box, CU_TENSOR_MAP_SWIZZLE_128B);
  }
  Params p;
  p.x = (const __nv_bfloat16*)d_in[0];      p.log_a = (const __nv_bfloat16*)d_in[1];
  p.a_im = (const __nv_bfloat16*)d_in[2];   p.c_re = (const __nv_bfloat16*)d_in[3];
  p.c_im = (const __nv_bfloat16*)d_in[4];   p.log_dt = (const __nv_bfloat16*)d_in[5];
  p.d_skip = (const __nv_bfloat16*)d_in[6]; p.w_down = (const __nv_bfloat16*)d_in[10];
  p.gate_w = (const __nv_bfloat16*)d_in[11];
  p.w_gate = (const __nv_bfloat16*)d_in[8]; p.w_up = (const __nv_bfloat16*)d_in[9];
  cudaFuncSetAttribute(gated_mix_kernel, cudaFuncAttributeMaxDynamicSharedMemorySize, SMEM_BYTES);
  gated_mix_kernel<<<132, 512, SMEM_BYTES>>>(p, tm_x, tm_wg, tm_wg3, tm_wu, tm_wu3, tm_wd, tm_out, tm_u, tm_xp, tm_ul);
}
```

```cpp
#include <cuda_runtime.h>
#include <cuda_bf16.h>
#include <cuda_fp16.h>
#include <cuda.h>
#include <stdint.h>

namespace {

constexpr int kL = 2048, kD = 512, kF = 1376;
constexpr int kClusters = 66;
constexpr int kSkewAt = 1;
constexpr int kConvHead = 5;
constexpr int kG2Head = 4;

constexpr uint32_t SLOT1   = 32768;
constexpr uint32_t OFF_P   = 0;
constexpr uint32_t OFF_W2  = 16384;
constexpr uint32_t OFF_RECV = OFF_W2 + 5 * 16384;
constexpr uint32_t OFF_HE  = 114688;
constexpr uint32_t OFF_A   = 163840;
constexpr uint32_t KT_COPY = 4208;
constexpr uint32_t KT_CH   = 2 * KT_COPY;
constexpr uint32_t OFF_PARK = OFF_A + 16896;
constexpr uint32_t OFF_KS  = OFF_A + 21504;
constexpr uint32_t OFF_KT23 = OFF_KS + 11840;
constexpr uint32_t OFF_GATE = OFF_A + 40960;
constexpr uint32_t KC_CH   = 2048;
constexpr uint32_t UT_PAR  = 2176;
constexpr uint32_t UT_CH   = 2 * UT_PAR;
constexpr uint32_t OFF_UT  = OFF_KS + 28672;
constexpr uint32_t OFF_HL5 = OFF_UT + UT_CH;
constexpr uint32_t OFF_BAR = OFF_UT + 4 * UT_CH;
constexpr uint32_t SMEM_BYTES = OFF_BAR + 512;

constexpr uint32_t B_FULL1 = OFF_BAR, B_RECV = B_FULL1 + 40;
constexpr uint32_t B_EMPTY1 = B_RECV + 8;
constexpr uint32_t B_SENDOK = B_EMPTY1 + 40;
constexpr uint32_t B_G1DONE = B_SENDOK + 8, B_EMPTYW = B_G1DONE + 8, B_C12 = B_EMPTYW + 40;
constexpr uint32_t B_EMPTYH = B_C12 + 8, B_PEMPTY = B_EMPTYH + 40, B_TAB = B_PEMPTY + 32;
constexpr uint32_t B_FULL3 = B_TAB + 16, B_DONE = B_FULL3 + 40;
constexpr uint32_t B_HL = B_DONE + 8, B_HE = B_HL + 48, B_WF = B_HE + 48, B_KH = B_WF + 8;
constexpr uint32_t B_UFULL = B_KH + 8, B_XTFULL = B_UFULL + 8, B_XTREAD = B_XTFULL + 8, B_W5 = B_XTREAD + 8, B_YFULL = B_W5 + 8;
constexpr uint32_t B_XOK = B_YFULL + 8, OFF_EPOCH = B_XOK + 8;
static_assert(OFF_EPOCH + 4 <= SMEM_BYTES && SMEM_BYTES <= 232448 && OFF_UT % 1024 == 0, "shared memory map");

__host__ __device__ constexpr int conv_ch(int c) { return (c + 1) & 3; }

enum { NB_SKEW = 1, NB_H0, NB_H1, NB_GO0, NB_GO1, NB_PFULL0, NB_PFULL1, NB_AUX, NB_UT, NB_KC0, NB_SENT, NB_ST0, NB_ST1, NB_INIT, NB_PAR };

constexpr int FLAG_STRIDE = 32;
constexpr int FL_H = 0, FL_U = 32, FL_Y = 40, FL_X = 44;

}

__device__ __align__(1024) uint8_t g_h[32 * 88 * 2048];
__device__ __align__(1024) uint8_t g_y[32 * 512 * 128];
__device__ __align__(1024) uint8_t g_u[2 * 512 * 2048];
__device__ __align__(256) uint32_t g_gate[kL];
__device__ uint32_t g_flags[48 * FLAG_STRIDE];

namespace {

__device__ __forceinline__ void mma_x(float (&d)[32], const uint32_t* a, uint32_t blo, int scale) {
  asm volatile("{\n.reg .pred p;\n.reg .b64 db;\nsetp.ne.b32 p, %37, 0;\nmov.b64 db, {%36, %38};\n"
    "wgmma.mma_async.sync.aligned.m64n64k16.f32.bf16.bf16 {%0,%1,%2,%3,%4,%5,%6,%7,%8,%9,%10,%11,%12,%13,%14,%15,%16,%17,%18,%19,%20,%21,%22,%23,%24,%25,%26,%27,%28,%29,%30,%31}, {%32,%33,%34,%35}, db, p, 1, 1, 1;\n}\n"
    : "+f"(d[0]),"+f"(d[1]),"+f"(d[2]),"+f"(d[3]),"+f"(d[4]),"+f"(d[5]),"+f"(d[6]),"+f"(d[7]),"+f"(d[8]),"+f"(d[9]),"+f"(d[10]),"+f"(d[11]),"+f"(d[12]),"+f"(d[13]),"+f"(d[14]),"+f"(d[15]),"+f"(d[16]),"+f"(d[17]),"+f"(d[18]),"+f"(d[19]),"+f"(d[20]),"+f"(d[21]),"+f"(d[22]),"+f"(d[23]),"+f"(d[24]),"+f"(d[25]),"+f"(d[26]),"+f"(d[27]),"+f"(d[28]),"+f"(d[29]),"+f"(d[30]),"+f"(d[31])
    : "r"(a[0]), "r"(a[1]), "r"(a[2]), "r"(a[3]), "r"(blo), "r"(scale), "n"(-2147483616));
}
__device__ __forceinline__ void mma_sum(float (&d)[4], const uint32_t* a, uint32_t blo, int scale) {
  asm volatile("{\n.reg .pred p;\n.reg .b64 db;\nsetp.ne.b32 p, %9, 0;\nmov.b64 db, {%8, %10};\n"
    "wgmma.mma_async.sync.aligned.m64n8k16.f32.bf16.bf16 {%0,%1,%2,%3}, {%4,%5,%6,%7}, db, p, 1, 1, 0;\n}\n"
    : "+f"(d[0]),"+f"(d[1]),"+f"(d[2]),"+f"(d[3])
    : "r"(a[0]), "r"(a[1]), "r"(a[2]), "r"(a[3]), "r"(blo), "r"(scale), "n"(8));
}
__device__ __forceinline__ void mma_g1(float (&d)[84], uint32_t alo, uint32_t blo, int scale) {
  asm volatile("{\n.reg .pred p;\n.reg .b64 da, db;\nsetp.ne.b32 p, %86, 0;\nmov.b64 da, {%84, %87};\nmov.b64 db, {%85, %88};\n"
    "wgmma.mma_async.sync.aligned.m64n168k16.f32.bf16.bf16 {%0,%1,%2,%3,%4,%5,%6,%7,%8,%9,%10,%11,%12,%13,%14,%15,%16,%17,%18,%19,%20,%21,%22,%23,%24,%25,%26,%27,%28,%29,%30,%31,%32,%33,%34,%35,%36,%37,%38,%39,%40,%41,%42,%43,%44,%45,%46,%47,%48,%49,%50,%51,%52,%53,%54,%55,%56,%57,%58,%59,%60,%61,%62,%63,%64,%65,%66,%67,%68,%69,%70,%71,%72,%73,%74,%75,%76,%77,%78,%79,%80,%81,%82,%83}, da, db, p, 1, 1, 0, 1;\n}\n"
    : "+f"(d[0]),"+f"(d[1]),"+f"(d[2]),"+f"(d[3]),"+f"(d[4]),"+f"(d[5]),"+f"(d[6]),"+f"(d[7]),"+f"(d[8]),"+f"(d[9]),"+f"(d[10]),"+f"(d[11]),"+f"(d[12]),"+f"(d[13]),"+f"(d[14]),"+f"(d[15]),"+f"(d[16]),"+f"(d[17]),"+f"(d[18]),"+f"(d[19]),"+f"(d[20]),"+f"(d[21]),"+f"(d[22]),"+f"(d[23]),"+f"(d[24]),"+f"(d[25]),"+f"(d[26]),"+f"(d[27]),"+f"(d[28]),"+f"(d[29]),"+f"(d[30]),"+f"(d[31]),"+f"(d[32]),"+f"(d[33]),"+f"(d[34]),"+f"(d[35]),"+f"(d[36]),"+f"(d[37]),"+f"(d[38]),"+f"(d[39]),"+f"(d[40]),"+f"(d[41]),"+f"(d[42]),"+f"(d[43]),"+f"(d[44]),"+f"(d[45]),"+f"(d[46]),"+f"(d[47]),"+f"(d[48]),"+f"(d[49]),"+f"(d[50]),"+f"(d[51]),"+f"(d[52]),"+f"(d[53]),"+f"(d[54]),"+f"(d[55]),"+f"(d[56]),"+f"(d[57]),"+f"(d[58]),"+f"(d[59]),"+f"(d[60]),"+f"(d[61]),"+f"(d[62]),"+f"(d[63]),"+f"(d[64]),"+f"(d[65]),"+f"(d[66]),"+f"(d[67]),"+f"(d[68]),"+f"(d[69]),"+f"(d[70]),"+f"(d[71]),"+f"(d[72]),"+f"(d[73]),"+f"(d[74]),"+f"(d[75]),"+f"(d[76]),"+f"(d[77]),"+f"(d[78]),"+f"(d[79]),"+f"(d[80]),"+f"(d[81]),"+f"(d[82]),"+f"(d[83])
    : "r"(alo), "r"(blo), "r"(scale), "n"(-2147483616), "n"(1073741888));
}
__device__ __forceinline__ void mma_g2(float (&d)[64], uint32_t alo, uint32_t blo, int scale) {
  asm volatile("{\n.reg .pred p;\n.reg .b64 da, db;\nsetp.ne.b32 p, %66, 0;\nmov.b64 da, {%64, %67};\nmov.b64 db, {%65, %68};\n"
    "wgmma.mma_async.sync.aligned.m64n128k16.f32.bf16.bf16 {%0,%1,%2,%3,%4,%5,%6,%7,%8,%9,%10,%11,%12,%13,%14,%15,%16,%17,%18,%19,%20,%21,%22,%23,%24,%25,%26,%27,%28,%29,%30,%31,%32,%33,%34,%35,%36,%37,%38,%39,%40,%41,%42,%43,%44,%45,%46,%47,%48,%49,%50,%51,%52,%53,%54,%55,%56,%57,%58,%59,%60,%61,%62,%63}, da, db, p, 1, 1, 0, 1;\n}\n"
    : "+f"(d[0]),"+f"(d[1]),"+f"(d[2]),"+f"(d[3]),"+f"(d[4]),"+f"(d[5]),"+f"(d[6]),"+f"(d[7]),"+f"(d[8]),"+f"(d[9]),"+f"(d[10]),"+f"(d[11]),"+f"(d[12]),"+f"(d[13]),"+f"(d[14]),"+f"(d[15]),"+f"(d[16]),"+f"(d[17]),"+f"(d[18]),"+f"(d[19]),"+f"(d[20]),"+f"(d[21]),"+f"(d[22]),"+f"(d[23]),"+f"(d[24]),"+f"(d[25]),"+f"(d[26]),"+f"(d[27]),"+f"(d[28]),"+f"(d[29]),"+f"(d[30]),"+f"(d[31]),"+f"(d[32]),"+f"(d[33]),"+f"(d[34]),"+f"(d[35]),"+f"(d[36]),"+f"(d[37]),"+f"(d[38]),"+f"(d[39]),"+f"(d[40]),"+f"(d[41]),"+f"(d[42]),"+f"(d[43]),"+f"(d[44]),"+f"(d[45]),"+f"(d[46]),"+f"(d[47]),"+f"(d[48]),"+f"(d[49]),"+f"(d[50]),"+f"(d[51]),"+f"(d[52]),"+f"(d[53]),"+f"(d[54]),"+f"(d[55]),"+f"(d[56]),"+f"(d[57]),"+f"(d[58]),"+f"(d[59]),"+f"(d[60]),"+f"(d[61]),"+f"(d[62]),"+f"(d[63])
    : "r"(alo), "r"(blo), "r"(scale), "n"(8), "n"(1073741888));
}
__device__ __forceinline__ void mma_kgen(float (&d)[24], uint32_t alo, uint32_t blo, int scale) {
  asm volatile("{\n.reg .pred p;\n.reg .b64 da, db;\nsetp.ne.b32 p, %26, 0;\nmov.b64 da, {%24, %27};\nmov.b64 db, {%25, %28};\n"
    "wgmma.mma_async.sync.aligned.m64n48k16.f32.f16.f16 {%0,%1,%2,%3,%4,%5,%6,%7,%8,%9,%10,%11,%12,%13,%14,%15,%16,%17,%18,%19,%20,%21,%22,%23}, da, db, p, 1, 1, 1, 1;\n}\n"
    : "+f"(d[0]),"+f"(d[1]),"+f"(d[2]),"+f"(d[3]),"+f"(d[4]),"+f"(d[5]),"+f"(d[6]),"+f"(d[7]),"+f"(d[8]),"+f"(d[9]),"+f"(d[10]),"+f"(d[11]),"+f"(d[12]),"+f"(d[13]),"+f"(d[14]),"+f"(d[15]),"+f"(d[16]),"+f"(d[17]),"+f"(d[18]),"+f"(d[19]),"+f"(d[20]),"+f"(d[21]),"+f"(d[22]),"+f"(d[23])
    : "r"(alo), "r"(blo), "r"(scale), "n"(128), "n"(128));
}
template<int N> __device__ __forceinline__ void mma_conv(float (&d)[64], uint32_t alo, uint32_t blo, int scale);
template<> __device__ __forceinline__ void mma_conv<8>(float (&d)[64], uint32_t alo, uint32_t blo, int scale) {
  asm volatile("{\n.reg .pred p;\n.reg .b64 da, db;\nsetp.ne.b32 p, %6, 0;\nmov.b64 da, {%4, %7};\nmov.b64 db, {%5, %8};\n"
    "wgmma.mma_async.sync.aligned.m64n8k16.f32.bf16.bf16 {%0,%1,%2,%3}, da, db, p, 1, 1, 1, 0;\n}\n"
    : "+f"(d[0]),"+f"(d[1]),"+f"(d[2]),"+f"(d[3])
    : "r"(alo), "r"(blo), "r"(scale), "n"(1), "n"(8));
}
template<> __device__ __forceinline__ void mma_conv<16>(float (&d)[64], uint32_t alo, uint32_t blo, int scale) {
  asm volatile("{\n.reg .pred p;\n.reg .b64 da, db;\nsetp.ne.b32 p, %10, 0;\nmov.b64 da, {%8, %11};\nmov.b64 db, {%9, %12};\n"
    "wgmma.mma_async.sync.aligned.m64n16k16.f32.bf16.bf16 {%0,%1,%2,%3,%4,%5,%6,%7}, da, db, p, 1, 1, 1, 0;\n}\n"
    : "+f"(d[0]),"+f"(d[1]),"+f"(d[2]),"+f"(d[3]),"+f"(d[4]),"+f"(d[5]),"+f"(d[6]),"+f"(d[7])
    : "r"(alo), "r"(blo), "r"(scale), "n"(1), "n"(8));
}
template<> __device__ __forceinline__ void mma_conv<24>(float (&d)[64], uint32_t alo, uint32_t blo, int scale) {
  asm volatile("{\n.reg .pred p;\n.reg .b64 da, db;\nsetp.ne.b32 p, %14, 0;\nmov.b64 da, {%12, %15};\nmov.b64 db, {%13, %16};\n"
    "wgmma.mma_async.sync.aligned.m64n24k16.f32.bf16.bf16 {%0,%1,%2,%3,%4,%5,%6,%7,%8,%9,%10,%11}, da, db, p, 1, 1, 1, 0;\n}\n"
    : "+f"(d[0]),"+f"(d[1]),"+f"(d[2]),"+f"(d[3]),"+f"(d[4]),"+f"(d[5]),"+f"(d[6]),"+f"(d[7]),"+f"(d[8]),"+f"(d[9]),"+f"(d[10]),"+f"(d[11])
    : "r"(alo), "r"(blo), "r"(scale), "n"(1), "n"(8));
}
template<> __device__ __forceinline__ void mma_conv<32>(float (&d)[64], uint32_t alo, uint32_t blo, int scale) {
  asm volatile("{\n.reg .pred p;\n.reg .b64 da, db;\nsetp.ne.b32 p, %18, 0;\nmov.b64 da, {%16, %19};\nmov.b64 db, {%17, %20};\n"
    "wgmma.mma_async.sync.aligned.m64n32k16.f32.bf16.bf16 {%0,%1,%2,%3,%4,%5,%6,%7,%8,%9,%10,%11,%12,%13,%14,%15}, da, db, p, 1, 1, 1, 0;\n}\n"
    : "+f"(d[0]),"+f"(d[1]),"+f"(d[2]),"+f"(d[3]),"+f"(d[4]),"+f"(d[5]),"+f"(d[6]),"+f"(d[7]),"+f"(d[8]),"+f"(d[9]),"+f"(d[10]),"+f"(d[11]),"+f"(d[12]),"+f"(d[13]),"+f"(d[14]),"+f"(d[15])
    : "r"(alo), "r"(blo), "r"(scale), "n"(1), "n"(8));
}
template<> __device__ __forceinline__ void mma_conv<40>(float (&d)[64], uint32_t alo, uint32_t blo, int scale) {
  asm volatile("{\n.reg .pred p;\n.reg .b64 da, db;\nsetp.ne.b32 p, %22, 0;\nmov.b64 da, {%20, %23};\nmov.b64 db, {%21, %24};\n"
    "wgmma.mma_async.sync.aligned.m64n40k16.f32.bf16.bf16 {%0,%1,%2,%3,%4,%5,%6,%7,%8,%9,%10,%11,%12,%13,%14,%15,%16,%17,%18,%19}, da, db, p, 1, 1, 1, 0;\n}\n"
    : "+f"(d[0]),"+f"(d[1]),"+f"(d[2]),"+f"(d[3]),"+f"(d[4]),"+f"(d[5]),"+f"(d[6]),"+f"(d[7]),"+f"(d[8]),"+f"(d[9]),"+f"(d[10]),"+f"(d[11]),"+f"(d[12]),"+f"(d[13]),"+f"(d[14]),"+f"(d[15]),"+f"(d[16]),"+f"(d[17]),"+f"(d[18]),"+f"(d[19])
    : "r"(alo), "r"(blo), "r"(scale), "n"(1), "n"(8));
}
template<> __device__ __forceinline__ void mma_conv<48>(float (&d)[64], uint32_t alo, uint32_t blo, int scale) {
  asm volatile("{\n.reg .pred p;\n.reg .b64 da, db;\nsetp.ne.b32 p, %26, 0;\nmov.b64 da, {%24, %27};\nmov.b64 db, {%25, %28};\n"
    "wgmma.mma_async.sync.aligned.m64n48k16.f32.bf16.bf16 {%0,%1,%2,%3,%4,%5,%6,%7,%8,%9,%10,%11,%12,%13,%14,%15,%16,%17,%18,%19,%20,%21,%22,%23}, da, db, p, 1, 1, 1, 0;\n}\n"
    : "+f"(d[0]),"+f"(d[1]),"+f"(d[2]),"+f"(d[3]),"+f"(d[4]),"+f"(d[5]),"+f"(d[6]),"+f"(d[7]),"+f"(d[8]),"+f"(d[9]),"+f"(d[10]),"+f"(d[11]),"+f"(d[12]),"+f"(d[13]),"+f"(d[14]),"+f"(d[15]),"+f"(d[16]),"+f"(d[17]),"+f"(d[18]),"+f"(d[19]),"+f"(d[20]),"+f"(d[21]),"+f"(d[22]),"+f"(d[23])
    : "r"(alo), "r"(blo), "r"(scale), "n"(1), "n"(8));
}
template<> __device__ __forceinline__ void mma_conv<56>(float (&d)[64], uint32_t alo, uint32_t blo, int scale) {
  asm volatile("{\n.reg .pred p;\n.reg .b64 da, db;\nsetp.ne.b32 p, %30, 0;\nmov.b64 da, {%28, %31};\nmov.b64 db, {%29, %32};\n"
    "wgmma.mma_async.sync.aligned.m64n56k16.f32.bf16.bf16 {%0,%1,%2,%3,%4,%5,%6,%7,%8,%9,%10,%11,%12,%13,%14,%15,%16,%17,%18,%19,%20,%21,%22,%23,%24,%25,%26,%27}, da, db, p, 1, 1, 1, 0;\n}\n"
    : "+f"(d[0]),"+f"(d[1]),"+f"(d[2]),"+f"(d[3]),"+f"(d[4]),"+f"(d[5]),"+f"(d[6]),"+f"(d[7]),"+f"(d[8]),"+f"(d[9]),"+f"(d[10]),"+f"(d[11]),"+f"(d[12]),"+f"(d[13]),"+f"(d[14]),"+f"(d[15]),"+f"(d[16]),"+f"(d[17]),"+f"(d[18]),"+f"(d[19]),"+f"(d[20]),"+f"(d[21]),"+f"(d[22]),"+f"(d[23]),"+f"(d[24]),"+f"(d[25]),"+f"(d[26]),"+f"(d[27])
    : "r"(alo), "r"(blo), "r"(scale), "n"(1), "n"(8));
}
template<> __device__ __forceinline__ void mma_conv<64>(float (&d)[64], uint32_t alo, uint32_t blo, int scale) {
  asm volatile("{\n.reg .pred p;\n.reg .b64 da, db;\nsetp.ne.b32 p, %34, 0;\nmov.b64 da, {%32, %35};\nmov.b64 db, {%33, %36};\n"
    "wgmma.mma_async.sync.aligned.m64n64k16.f32.bf16.bf16 {%0,%1,%2,%3,%4,%5,%6,%7,%8,%9,%10,%11,%12,%13,%14,%15,%16,%17,%18,%19,%20,%21,%22,%23,%24,%25,%26,%27,%28,%29,%30,%31}, da, db, p, 1, 1, 1, 0;\n}\n"
    : "+f"(d[0]),"+f"(d[1]),"+f"(d[2]),"+f"(d[3]),"+f"(d[4]),"+f"(d[5]),"+f"(d[6]),"+f"(d[7]),"+f"(d[8]),"+f"(d[9]),"+f"(d[10]),"+f"(d[11]),"+f"(d[12]),"+f"(d[13]),"+f"(d[14]),"+f"(d[15]),"+f"(d[16]),"+f"(d[17]),"+f"(d[18]),"+f"(d[19]),"+f"(d[20]),"+f"(d[21]),"+f"(d[22]),"+f"(d[23]),"+f"(d[24]),"+f"(d[25]),"+f"(d[26]),"+f"(d[27]),"+f"(d[28]),"+f"(d[29]),"+f"(d[30]),"+f"(d[31])
    : "r"(alo), "r"(blo), "r"(scale), "n"(1), "n"(8));
}
template<> __device__ __forceinline__ void mma_conv<72>(float (&d)[64], uint32_t alo, uint32_t blo, int scale) {
  asm volatile("{\n.reg .pred p;\n.reg .b64 da, db;\nsetp.ne.b32 p, %38, 0;\nmov.b64 da, {%36, %39};\nmov.b64 db, {%37, %40};\n"
    "wgmma.mma_async.sync.aligned.m64n72k16.f32.bf16.bf16 {%0,%1,%2,%3,%4,%5,%6,%7,%8,%9,%10,%11,%12,%13,%14,%15,%16,%17,%18,%19,%20,%21,%22,%23,%24,%25,%26,%27,%28,%29,%30,%31,%32,%33,%34,%35}, da, db, p, 1, 1, 1, 0;\n}\n"
    : "+f"(d[0]),"+f"(d[1]),"+f"(d[2]),"+f"(d[3]),"+f"(d[4]),"+f"(d[5]),"+f"(d[6]),"+f"(d[7]),"+f"(d[8]),"+f"(d[9]),"+f"(d[10]),"+f"(d[11]),"+f"(d[12]),"+f"(d[13]),"+f"(d[14]),"+f"(d[15]),"+f"(d[16]),"+f"(d[17]),"+f"(d[18]),"+f"(d[19]),"+f"(d[20]),"+f"(d[21]),"+f"(d[22]),"+f"(d[23]),"+f"(d[24]),"+f"(d[25]),"+f"(d[26]),"+f"(d[27]),"+f"(d[28]),"+f"(d[29]),"+f"(d[30]),"+f"(d[31]),"+f"(d[32]),"+f"(d[33]),"+f"(d[34]),"+f"(d[35])
    : "r"(alo), "r"(blo), "r"(scale), "n"(1), "n"(8));
}
template<> __device__ __forceinline__ void mma_conv<80>(float (&d)[64], uint32_t alo, uint32_t blo, int scale) {
  asm volatile("{\n.reg .pred p;\n.reg .b64 da, db;\nsetp.ne.b32 p, %42, 0;\nmov.b64 da, {%40, %43};\nmov.b64 db, {%41, %44};\n"
    "wgmma.mma_async.sync.aligned.m64n80k16.f32.bf16.bf16 {%0,%1,%2,%3,%4,%5,%6,%7,%8,%9,%10,%11,%12,%13,%14,%15,%16,%17,%18,%19,%20,%21,%22,%23,%24,%25,%26,%27,%28,%29,%30,%31,%32,%33,%34,%35,%36,%37,%38,%39}, da, db, p, 1, 1, 1, 0;\n}\n"
    : "+f"(d[0]),"+f"(d[1]),"+f"(d[2]),"+f"(d[3]),"+f"(d[4]),"+f"(d[5]),"+f"(d[6]),"+f"(d[7]),"+f"(d[8]),"+f"(d[9]),"+f"(d[10]),"+f"(d[11]),"+f"(d[12]),"+f"(d[13]),"+f"(d[14]),"+f"(d[15]),"+f"(d[16]),"+f"(d[17]),"+f"(d[18]),"+f"(d[19]),"+f"(d[20]),"+f"(d[21]),"+f"(d[22]),"+f"(d[23]),"+f"(d[24]),"+f"(d[25]),"+f"(d[26]),"+f"(d[27]),"+f"(d[28]),"+f"(d[29]),"+f"(d[30]),"+f"(d[31]),"+f"(d[32]),"+f"(d[33]),"+f"(d[34]),"+f"(d[35]),"+f"(d[36]),"+f"(d[37]),"+f"(d[38]),"+f"(d[39])
    : "r"(alo), "r"(blo), "r"(scale), "n"(1), "n"(8));
}
template<> __device__ __forceinline__ void mma_conv<88>(float (&d)[64], uint32_t alo, uint32_t blo, int scale) {
  asm volatile("{\n.reg .pred p;\n.reg .b64 da, db;\nsetp.ne.b32 p, %46, 0;\nmov.b64 da, {%44, %47};\nmov.b64 db, {%45, %48};\n"
    "wgmma.mma_async.sync.aligned.m64n88k16.f32.bf16.bf16 {%0,%1,%2,%3,%4,%5,%6,%7,%8,%9,%10,%11,%12,%13,%14,%15,%16,%17,%18,%19,%20,%21,%22,%23,%24,%25,%26,%27,%28,%29,%30,%31,%32,%33,%34,%35,%36,%37,%38,%39,%40,%41,%42,%43}, da, db, p, 1, 1, 1, 0;\n}\n"
    : "+f"(d[0]),"+f"(d[1]),"+f"(d[2]),"+f"(d[3]),"+f"(d[4]),"+f"(d[5]),"+f"(d[6]),"+f"(d[7]),"+f"(d[8]),"+f"(d[9]),"+f"(d[10]),"+f"(d[11]),"+f"(d[12]),"+f"(d[13]),"+f"(d[14]),"+f"(d[15]),"+f"(d[16]),"+f"(d[17]),"+f"(d[18]),"+f"(d[19]),"+f"(d[20]),"+f"(d[21]),"+f"(d[22]),"+f"(d[23]),"+f"(d[24]),"+f"(d[25]),"+f"(d[26]),"+f"(d[27]),"+f"(d[28]),"+f"(d[29]),"+f"(d[30]),"+f"(d[31]),"+f"(d[32]),"+f"(d[33]),"+f"(d[34]),"+f"(d[35]),"+f"(d[36]),"+f"(d[37]),"+f"(d[38]),"+f"(d[39]),"+f"(d[40]),"+f"(d[41]),"+f"(d[42]),"+f"(d[43])
    : "r"(alo), "r"(blo), "r"(scale), "n"(1), "n"(8));
}
template<> __device__ __forceinline__ void mma_conv<96>(float (&d)[64], uint32_t alo, uint32_t blo, int scale) {
  asm volatile("{\n.reg .pred p;\n.reg .b64 da, db;\nsetp.ne.b32 p, %50, 0;\nmov.b64 da, {%48, %51};\nmov.b64 db, {%49, %52};\n"
    "wgmma.mma_async.sync.aligned.m64n96k16.f32.bf16.bf16 {%0,%1,%2,%3,%4,%5,%6,%7,%8,%9,%10,%11,%12,%13,%14,%15,%16,%17,%18,%19,%20,%21,%22,%23,%24,%25,%26,%27,%28,%29,%30,%31,%32,%33,%34,%35,%36,%37,%38,%39,%40,%41,%42,%43,%44,%45,%46,%47}, da, db, p, 1, 1, 1, 0;\n}\n"
    : "+f"(d[0]),"+f"(d[1]),"+f"(d[2]),"+f"(d[3]),"+f"(d[4]),"+f"(d[5]),"+f"(d[6]),"+f"(d[7]),"+f"(d[8]),"+f"(d[9]),"+f"(d[10]),"+f"(d[11]),"+f"(d[12]),"+f"(d[13]),"+f"(d[14]),"+f"(d[15]),"+f"(d[16]),"+f"(d[17]),"+f"(d[18]),"+f"(d[19]),"+f"(d[20]),"+f"(d[21]),"+f"(d[22]),"+f"(d[23]),"+f"(d[24]),"+f"(d[25]),"+f"(d[26]),"+f"(d[27]),"+f"(d[28]),"+f"(d[29]),"+f"(d[30]),"+f"(d[31]),"+f"(d[32]),"+f"(d[33]),"+f"(d[34]),"+f"(d[35]),"+f"(d[36]),"+f"(d[37]),"+f"(d[38]),"+f"(d[39]),"+f"(d[40]),"+f"(d[41]),"+f"(d[42]),"+f"(d[43]),"+f"(d[44]),"+f"(d[45]),"+f"(d[46]),"+f"(d[47])
    : "r"(alo), "r"(blo), "r"(scale), "n"(1), "n"(8));
}
template<> __device__ __forceinline__ void mma_conv<104>(float (&d)[64], uint32_t alo, uint32_t blo, int scale) {
  asm volatile("{\n.reg .pred p;\n.reg .b64 da, db;\nsetp.ne.b32 p, %54, 0;\nmov.b64 da, {%52, %55};\nmov.b64 db, {%53, %56};\n"
    "wgmma.mma_async.sync.aligned.m64n104k16.f32.bf16.bf16 {%0,%1,%2,%3,%4,%5,%6,%7,%8,%9,%10,%11,%12,%13,%14,%15,%16,%17,%18,%19,%20,%21,%22,%23,%24,%25,%26,%27,%28,%29,%30,%31,%32,%33,%34,%35,%36,%37,%38,%39,%40,%41,%42,%43,%44,%45,%46,%47,%48,%49,%50,%51}, da, db, p, 1, 1, 1, 0;\n}\n"
    : "+f"(d[0]),"+f"(d[1]),"+f"(d[2]),"+f"(d[3]),"+f"(d[4]),"+f"(d[5]),"+f"(d[6]),"+f"(d[7]),"+f"(d[8]),"+f"(d[9]),"+f"(d[10]),"+f"(d[11]),"+f"(d[12]),"+f"(d[13]),"+f"(d[14]),"+f"(d[15]),"+f"(d[16]),"+f"(d[17]),"+f"(d[18]),"+f"(d[19]),"+f"(d[20]),"+f"(d[21]),"+f"(d[22]),"+f"(d[23]),"+f"(d[24]),"+f"(d[25]),"+f"(d[26]),"+f"(d[27]),"+f"(d[28]),"+f"(d[29]),"+f"(d[30]),"+f"(d[31]),"+f"(d[32]),"+f"(d[33]),"+f"(d[34]),"+f"(d[35]),"+f"(d[36]),"+f"(d[37]),"+f"(d[38]),"+f"(d[39]),"+f"(d[40]),"+f"(d[41]),"+f"(d[42]),"+f"(d[43]),"+f"(d[44]),"+f"(d[45]),"+f"(d[46]),"+f"(d[47]),"+f"(d[48]),"+f"(d[49]),"+f"(d[50]),"+f"(d[51])
    : "r"(alo), "r"(blo), "r"(scale), "n"(1), "n"(8));
}
template<> __device__ __forceinline__ void mma_conv<112>(float (&d)[64], uint32_t alo, uint32_t blo, int scale) {
  asm volatile("{\n.reg .pred p;\n.reg .b64 da, db;\nsetp.ne.b32 p, %58, 0;\nmov.b64 da, {%56, %59};\nmov.b64 db, {%57, %60};\n"
    "wgmma.mma_async.sync.aligned.m64n112k16.f32.bf16.bf16 {%0,%1,%2,%3,%4,%5,%6,%7,%8,%9,%10,%11,%12,%13,%14,%15,%16,%17,%18,%19,%20,%21,%22,%23,%24,%25,%26,%27,%28,%29,%30,%31,%32,%33,%34,%35,%36,%37,%38,%39,%40,%41,%42,%43,%44,%45,%46,%47,%48,%49,%50,%51,%52,%53,%54,%55}, da, db, p, 1, 1, 1, 0;\n}\n"
    : "+f"(d[0]),"+f"(d[1]),"+f"(d[2]),"+f"(d[3]),"+f"(d[4]),"+f"(d[5]),"+f"(d[6]),"+f"(d[7]),"+f"(d[8]),"+f"(d[9]),"+f"(d[10]),"+f"(d[11]),"+f"(d[12]),"+f"(d[13]),"+f"(d[14]),"+f"(d[15]),"+f"(d[16]),"+f"(d[17]),"+f"(d[18]),"+f"(d[19]),"+f"(d[20]),"+f"(d[21]),"+f"(d[22]),"+f"(d[23]),"+f"(d[24]),"+f"(d[25]),"+f"(d[26]),"+f"(d[27]),"+f"(d[28]),"+f"(d[29]),"+f"(d[30]),"+f"(d[31]),"+f"(d[32]),"+f"(d[33]),"+f"(d[34]),"+f"(d[35]),"+f"(d[36]),"+f"(d[37]),"+f"(d[38]),"+f"(d[39]),"+f"(d[40]),"+f"(d[41]),"+f"(d[42]),"+f"(d[43]),"+f"(d[44]),"+f"(d[45]),"+f"(d[46]),"+f"(d[47]),"+f"(d[48]),"+f"(d[49]),"+f"(d[50]),"+f"(d[51]),"+f"(d[52]),"+f"(d[53]),"+f"(d[54]),"+f"(d[55])
    : "r"(alo), "r"(blo), "r"(scale), "n"(1), "n"(8));
}
template<> __device__ __forceinline__ void mma_conv<120>(float (&d)[64], uint32_t alo, uint32_t blo, int scale) {
  asm volatile("{\n.reg .pred p;\n.reg .b64 da, db;\nsetp.ne.b32 p, %62, 0;\nmov.b64 da, {%60, %63};\nmov.b64 db, {%61, %64};\n"
    "wgmma.mma_async.sync.aligned.m64n120k16.f32.bf16.bf16 {%0,%1,%2,%3,%4,%5,%6,%7,%8,%9,%10,%11,%12,%13,%14,%15,%16,%17,%18,%19,%20,%21,%22,%23,%24,%25,%26,%27,%28,%29,%30,%31,%32,%33,%34,%35,%36,%37,%38,%39,%40,%41,%42,%43,%44,%45,%46,%47,%48,%49,%50,%51,%52,%53,%54,%55,%56,%57,%58,%59}, da, db, p, 1, 1, 1, 0;\n}\n"
    : "+f"(d[0]),"+f"(d[1]),"+f"(d[2]),"+f"(d[3]),"+f"(d[4]),"+f"(d[5]),"+f"(d[6]),"+f"(d[7]),"+f"(d[8]),"+f"(d[9]),"+f"(d[10]),"+f"(d[11]),"+f"(d[12]),"+f"(d[13]),"+f"(d[14]),"+f"(d[15]),"+f"(d[16]),"+f"(d[17]),"+f"(d[18]),"+f"(d[19]),"+f"(d[20]),"+f"(d[21]),"+f"(d[22]),"+f"(d[23]),"+f"(d[24]),"+f"(d[25]),"+f"(d[26]),"+f"(d[27]),"+f"(d[28]),"+f"(d[29]),"+f"(d[30]),"+f"(d[31]),"+f"(d[32]),"+f"(d[33]),"+f"(d[34]),"+f"(d[35]),"+f"(d[36]),"+f"(d[37]),"+f"(d[38]),"+f"(d[39]),"+f"(d[40]),"+f"(d[41]),"+f"(d[42]),"+f"(d[43]),"+f"(d[44]),"+f"(d[45]),"+f"(d[46]),"+f"(d[47]),"+f"(d[48]),"+f"(d[49]),"+f"(d[50]),"+f"(d[51]),"+f"(d[52]),"+f"(d[53]),"+f"(d[54]),"+f"(d[55]),"+f"(d[56]),"+f"(d[57]),"+f"(d[58]),"+f"(d[59])
    : "r"(alo), "r"(blo), "r"(scale), "n"(1), "n"(8));
}
template<> __device__ __forceinline__ void mma_conv<128>(float (&d)[64], uint32_t alo, uint32_t blo, int scale) {
  asm volatile("{\n.reg .pred p;\n.reg .b64 da, db;\nsetp.ne.b32 p, %66, 0;\nmov.b64 da, {%64, %67};\nmov.b64 db, {%65, %68};\n"
    "wgmma.mma_async.sync.aligned.m64n128k16.f32.bf16.bf16 {%0,%1,%2,%3,%4,%5,%6,%7,%8,%9,%10,%11,%12,%13,%14,%15,%16,%17,%18,%19,%20,%21,%22,%23,%24,%25,%26,%27,%28,%29,%30,%31,%32,%33,%34,%35,%36,%37,%38,%39,%40,%41,%42,%43,%44,%45,%46,%47,%48,%49,%50,%51,%52,%53,%54,%55,%56,%57,%58,%59,%60,%61,%62,%63}, da, db, p, 1, 1, 1, 0;\n}\n"
    : "+f"(d[0]),"+f"(d[1]),"+f"(d[2]),"+f"(d[3]),"+f"(d[4]),"+f"(d[5]),"+f"(d[6]),"+f"(d[7]),"+f"(d[8]),"+f"(d[9]),"+f"(d[10]),"+f"(d[11]),"+f"(d[12]),"+f"(d[13]),"+f"(d[14]),"+f"(d[15]),"+f"(d[16]),"+f"(d[17]),"+f"(d[18]),"+f"(d[19]),"+f"(d[20]),"+f"(d[21]),"+f"(d[22]),"+f"(d[23]),"+f"(d[24]),"+f"(d[25]),"+f"(d[26]),"+f"(d[27]),"+f"(d[28]),"+f"(d[29]),"+f"(d[30]),"+f"(d[31]),"+f"(d[32]),"+f"(d[33]),"+f"(d[34]),"+f"(d[35]),"+f"(d[36]),"+f"(d[37]),"+f"(d[38]),"+f"(d[39]),"+f"(d[40]),"+f"(d[41]),"+f"(d[42]),"+f"(d[43]),"+f"(d[44]),"+f"(d[45]),"+f"(d[46]),"+f"(d[47]),"+f"(d[48]),"+f"(d[49]),"+f"(d[50]),"+f"(d[51]),"+f"(d[52]),"+f"(d[53]),"+f"(d[54]),"+f"(d[55]),"+f"(d[56]),"+f"(d[57]),"+f"(d[58]),"+f"(d[59]),"+f"(d[60]),"+f"(d[61]),"+f"(d[62]),"+f"(d[63])
    : "r"(alo), "r"(blo), "r"(scale), "n"(1), "n"(8));
}

__device__ __forceinline__ void wg_fence() { asm volatile("wgmma.fence.sync.aligned;" ::: "memory"); }
__device__ __forceinline__ void wg_commit() { asm volatile("wgmma.commit_group.sync.aligned;" ::: "memory"); }
template <int N> __device__ __forceinline__ void wg_wait() { asm volatile("wgmma.wait_group.sync.aligned %0;" ::"n"(N) : "memory"); }
template <int N> __device__ __forceinline__ void pin(float (&d)[N]) {
#pragma unroll
  for (int i = 0; i < N; i++) asm volatile("" : "+f"(d[i])::"memory");
}

__device__ __forceinline__ void mbar_init(uint32_t b, int c) { asm volatile("mbarrier.init.shared::cta.b64 [%0], %1;" ::"r"(b), "r"(c) : "memory"); }
__device__ __forceinline__ void mbar_arrive(uint32_t b) { asm volatile("mbarrier.arrive.shared::cta.b64 _, [%0];" ::"r"(b) : "memory"); }
__device__ __forceinline__ void mbar_expect(uint32_t b, uint32_t bytes) { asm volatile("mbarrier.arrive.expect_tx.shared::cta.b64 _, [%0], %1;" ::"r"(b), "r"(bytes) : "memory"); }
__device__ __forceinline__ void mbar_wait(uint32_t b, uint32_t parity) {
  asm volatile(
      "{\n.reg .pred p;\n.reg .u32 n;\n"
      "mbarrier.try_wait.parity.shared::cta.b64 p, [%0], %1;\n@p bra DONE;\nmov.u32 n, 0;\n"
      "W:\nmbarrier.try_wait.parity.shared::cta.b64 p, [%0], %1, 2000;\n@p bra DONE;\n"
      "add.u32 n, n, 1;\nsetp.lt.u32 p, n, 1000000;\n@p bra W;\ntrap;\nDONE:\n}\n" ::"r"(b), "r"(parity) : "memory");
}
__device__ __forceinline__ void cluster_wait() { asm volatile("barrier.cluster.wait.aligned;" ::: "memory"); }
__device__ __forceinline__ void nb_sync(int id, int n) { asm volatile("bar.sync %0, %1;" ::"r"(id), "r"(n) : "memory"); }
__device__ __forceinline__ void nb_sync_if(int p, int id, int n) {
  asm volatile("{\n.reg .pred p;\nsetp.ne.b32 p, %2, 0;\n@p bar.sync %0, %1;\n}\n" ::"r"(id), "r"(n), "r"(p) : "memory");
}
__device__ __forceinline__ void nb_arrive(int id, int n) { asm volatile("bar.arrive %0, %1;" ::"r"(id), "r"(n) : "memory"); }
__device__ __forceinline__ void fence_async_smem() { asm volatile("fence.proxy.async.shared::cta;" ::: "memory"); }
__device__ __forceinline__ void fence_async_all() { asm volatile("fence.proxy.async;" ::: "memory"); }

__device__ __forceinline__ void flag_signal(int f, uint32_t inc) {
  fence_async_all();
  asm volatile("red.relaxed.gpu.global.add.u32 [%0], %1;" ::"l"(g_flags + f * FLAG_STRIDE), "r"(inc) : "memory");
}
__device__ __forceinline__ uint32_t flag_peek(const uint32_t* f) {
  uint32_t v;
  asm volatile("ld.relaxed.gpu.global.u32 %0, [%1];" : "=r"(v) : "l"(f) : "memory");
  return v;
}
__device__ __forceinline__ void flag_wait(int idx, uint32_t target) {
  const uint32_t* f = g_flags + idx * FLAG_STRIDE;
#pragma unroll 1
  for (int i = 0; (int32_t)(flag_peek(f) - target) < 0; i++)
    if (i == 20000000) __trap();
  asm volatile("fence.acquire.gpu;" ::: "memory");
  asm volatile("fence.proxy.async.global;" ::: "memory");
}

__device__ __forceinline__ void tma2d(uint32_t dst, const CUtensorMap* m, uint32_t bar, int c0, int c1) {
  asm volatile("cp.async.bulk.tensor.2d.shared::cluster.global.mbarrier::complete_tx::bytes [%0], [%1, {%3, %4}], [%2];"
               ::"r"(dst), "l"(m), "r"(bar), "r"(c0), "r"(c1) : "memory");
}
__device__ __forceinline__ void tma3d(uint32_t dst, const CUtensorMap* m, uint32_t bar, int c0, int c1, int c2) {
  asm volatile("cp.async.bulk.tensor.3d.shared::cluster.global.mbarrier::complete_tx::bytes [%0], [%1, {%3, %4, %5}], [%2];"
               ::"r"(dst), "l"(m), "r"(bar), "r"(c0), "r"(c1), "r"(c2) : "memory");
}
__device__ __forceinline__ void tma2d_pair(uint32_t dst, const CUtensorMap* m, uint32_t bar, int c0, int c1) {
  asm volatile("cp.async.bulk.tensor.2d.shared::cluster.global.mbarrier::complete_tx::bytes.multicast::cluster [%0], [%1, {%3, %4}], [%2], %5;"
               ::"r"(dst), "l"(m), "r"(bar), "r"(c0), "r"(c1), "h"((uint16_t)3) : "memory");
}
__device__ __forceinline__ void tma3d_pair(uint32_t dst, const CUtensorMap* m, uint32_t bar, int c0, int c1, int c2) {
  asm volatile("cp.async.bulk.tensor.3d.shared::cluster.global.mbarrier::complete_tx::bytes.multicast::cluster [%0], [%1, {%3, %4, %5}], [%2], %6;"
               ::"r"(dst), "l"(m), "r"(bar), "r"(c0), "r"(c1), "r"(c2), "h"((uint16_t)3) : "memory");
}
__device__ __forceinline__ void mbar_arrive_cluster(uint32_t b) { asm volatile("mbarrier.arrive.shared::cluster.b64 _, [%0];" ::"r"(b) : "memory"); }
__device__ __forceinline__ void tma4d(uint32_t dst, const CUtensorMap* m, uint32_t bar, int c0, int c1, int c2, int c3) {
  asm volatile("cp.async.bulk.tensor.4d.shared::cluster.global.mbarrier::complete_tx::bytes [%0], [%1, {%3, %4, %5, %6}], [%2];"
               ::"r"(dst), "l"(m), "r"(bar), "r"(c0), "r"(c1), "r"(c2), "r"(c3) : "memory");
}
__device__ __forceinline__ void tma3d_store(const CUtensorMap* m, uint32_t src, int c0, int c1, int c2) {
  asm volatile("cp.async.bulk.tensor.3d.global.shared::cta.bulk_group [%0, {%2, %3, %4}], [%1];"
               ::"l"(m), "r"(src), "r"(c0), "r"(c1), "r"(c2) : "memory");
}
__device__ __forceinline__ void bulk_load(uint32_t dst, const void* src, uint32_t bytes, uint32_t bar) {
  asm volatile("cp.async.bulk.shared::cluster.global.mbarrier::complete_tx::bytes [%0], [%1], %2, [%3];"
               ::"r"(dst), "l"(src), "r"(bytes), "r"(bar) : "memory");
}
__device__ __forceinline__ void cp_async16(uint32_t dst, const void* src) {
  asm volatile("cp.async.cg.shared.global [%0], [%1], 16;" ::"r"(dst), "l"(src) : "memory");
}
__device__ __forceinline__ int selp(int a, int b, bool c) {
  int r;
  asm("{\n.reg .pred p;\nsetp.ne.b32 p, %3, 0;\nselp.b32 %0, %1, %2, p;\n}\n" : "=r"(r) : "r"(a), "r"(b), "r"((int)c));
  return r;
}
template <int FROM, int TO> __device__ __forceinline__ void init_barriers(uint32_t base) {
#pragma unroll
  for (int i = FROM; i < TO; i++) mbar_init(base + 8 * i, i < 6 ? 1 : i < 11 ? 16 : i < 19 ? 8 : i < 30 ? 4 : i < 35 ? 2 : i == 35 ? 15 : 1);
}
__device__ __forceinline__ void sched_fence(uint32_t v, uint32_t other) {
  asm volatile("{\n.reg .pred p;\nsetp.ne.u32 p, %0, %1;\n@p bra OK;\ntrap;\nOK:\n}\n" ::"r"(v), "r"(other) : "memory");
}
__device__ __forceinline__ bool elect() {
  uint32_t p;
  asm volatile("{\n.reg .pred p;\nelect.sync _|p, 0xffffffff;\nselp.b32 %0, 1, 0, p;\n}\n" : "=r"(p));
  return p;
}

__device__ __forceinline__ uint32_t pack_bf16(float lo, float hi) { uint32_t r; asm("cvt.rn.bf16x2.f32 %0, %1, %2;" : "=r"(r) : "f"(hi), "f"(lo)); return r; }
__device__ __forceinline__ uint32_t pack_f16(float lo, float hi) { uint32_t r; asm("cvt.rn.f16x2.f32 %0, %1, %2;" : "=r"(r) : "f"(hi), "f"(lo)); return r; }
__device__ __forceinline__ uint32_t bmul2(uint32_t a, uint32_t b) { uint32_t r; asm("mul.rn.bf16x2 %0, %1, %2;" : "=r"(r) : "r"(a), "r"(b)); return r; }
__device__ __forceinline__ uint32_t badd2(uint32_t a, uint32_t b) { uint32_t r; asm("add.rn.bf16x2 %0, %1, %2;" : "=r"(r) : "r"(a), "r"(b)); return r; }
__device__ __forceinline__ uint32_t bfma2(uint32_t a, uint32_t b, uint32_t c) { uint32_t r; asm("fma.rn.bf16x2 %0, %1, %2, %3;" : "=r"(r) : "r"(a), "r"(b), "r"(c)); return r; }
__device__ __forceinline__ float bf_lo(uint32_t w) { return __uint_as_float(w << 16); }
__device__ __forceinline__ float bf_hi(uint32_t w) { return __uint_as_float(w & 0xffff0000u); }
__device__ __forceinline__ float bf_round(float v) { return __bfloat162float(__float2bfloat16_rn(v)); }

__device__ __forceinline__ void sts128(uint32_t a, uint32_t x, uint32_t y, uint32_t z, uint32_t w) { asm volatile("st.shared.v4.u32 [%0], {%1, %2, %3, %4};" ::"r"(a), "r"(x), "r"(y), "r"(z), "r"(w) : "memory"); }
__device__ __forceinline__ void sts32(uint32_t a, uint32_t x) { asm volatile("st.shared.u32 [%0], %1;" ::"r"(a), "r"(x) : "memory"); }
__device__ __forceinline__ void sts16(uint32_t a, uint32_t x) { asm volatile("st.shared.u16 [%0], %1;" ::"r"(a), "h"((uint16_t)x) : "memory"); }
__device__ __forceinline__ void stsf(uint32_t a, float x) { asm volatile("st.shared.f32 [%0], %1;" ::"r"(a), "f"(x) : "memory"); }
__device__ __forceinline__ uint32_t lds32(uint32_t a) { uint32_t v; asm volatile("ld.shared.u32 %0, [%1];" : "=r"(v) : "r"(a) : "memory"); return v; }
__device__ __forceinline__ uint32_t lds16(uint32_t a) { uint16_t v; asm volatile("ld.shared.u16 %0, [%1];" : "=h"(v) : "r"(a) : "memory"); return v; }
__device__ __forceinline__ float ldsf(uint32_t a) { float v; asm volatile("ld.shared.f32 %0, [%1];" : "=f"(v) : "r"(a) : "memory"); return v; }
__device__ __forceinline__ float2 ldsf2(uint32_t a) { float2 v; asm volatile("ld.shared.v2.f32 {%0, %1}, [%2];" : "=f"(v.x), "=f"(v.y) : "r"(a) : "memory"); return v; }
__device__ __forceinline__ float4 ldsf4(uint32_t a) { float4 v; asm volatile("ld.shared.v4.f32 {%0, %1, %2, %3}, [%4];" : "=f"(v.x), "=f"(v.y), "=f"(v.z), "=f"(v.w) : "r"(a) : "memory"); return v; }
__device__ __forceinline__ void stsm4(uint32_t a, uint32_t r0, uint32_t r1, uint32_t r2, uint32_t r3) { asm volatile("stmatrix.sync.aligned.m8n8.x4.shared.b16 [%0], {%1, %2, %3, %4};" ::"r"(a), "r"(r0), "r"(r1), "r"(r2), "r"(r3) : "memory"); }
__device__ __forceinline__ void stsm4t(uint32_t a, uint32_t r0, uint32_t r1, uint32_t r2, uint32_t r3) { asm volatile("stmatrix.sync.aligned.m8n8.x4.trans.shared.b16 [%0], {%1, %2, %3, %4};" ::"r"(a), "r"(r0), "r"(r1), "r"(r2), "r"(r3) : "memory"); }
__device__ __forceinline__ void ldsm4(uint32_t a, uint32_t* r) { asm volatile("ldmatrix.sync.aligned.m8n8.x4.shared.b16 {%0, %1, %2, %3}, [%4];" : "=r"(r[0]), "=r"(r[1]), "=r"(r[2]), "=r"(r[3]) : "r"(a) : "memory"); }
__device__ __forceinline__ void ldsm4t(uint32_t a, uint32_t* r) { asm volatile("ldmatrix.sync.aligned.m8n8.x4.trans.shared.b16 {%0, %1, %2, %3}, [%4];" : "=r"(r[0]), "=r"(r[1]), "=r"(r[2]), "=r"(r[3]) : "r"(a) : "memory"); }

__device__ __forceinline__ float swiglu(float g, float u) {
  const float hg = 0.5f * g, q = hg * u;
  float th;
  asm("tanh.approx.f32 %0, %1;" : "=f"(th) : "f"(hg));
  return fmaf(q, th, q);
}

struct cf { float r, i; };
__device__ __forceinline__ cf cmul(cf a, cf b) { return {a.r * b.r - a.i * b.i, a.r * b.i + a.i * b.r}; }
__device__ __forceinline__ cf csq(cf a) { return {a.r * a.r - a.i * a.i, (a.r + a.r) * a.i}; }
__device__ __forceinline__ cf cpow_seed(float a2, float beta, float p) {
  float e;
  asm("ex2.approx.ftz.f32 %0, %1;" : "=f"(e) : "f"(a2 * p));
  const float th = beta * p;
  return {e * __cosf(th), e * __sinf(th)};
}
__device__ __forceinline__ void hcmul(uint32_t r, uint32_t i, uint32_t w, uint32_t& ro, uint32_t& io) {
  const __half2 hr = *reinterpret_cast<__half2*>(&r), hi = *reinterpret_cast<__half2*>(&i), hw = *reinterpret_cast<__half2*>(&w);
  const __half2 hwr = __low2half2(hw), hwi = __high2half2(hw);
  __half2 a = __hfma2(hr, hwr, __hneg2(__hmul2(hi, hwi)));
  __half2 b = __hfma2(hr, hwi, __hmul2(hi, hwr));
  ro = *reinterpret_cast<uint32_t*>(&a);
  io = *reinterpret_cast<uint32_t*>(&b);
}

struct Modes {
  uint32_t la, ai, cr, ci;
  uint32_t e;
  float dt;
};
__device__ __forceinline__ Modes load_modes(uint32_t park, int lc, int odd_cta, int mu) {
  Modes m;
  const uint32_t a = park + 256 * lc + 4 * mu, b = park + 4224 + 8 * odd_cta + 2 * lc;
  m.la = lds32(a); m.ai = lds32(a + 1024); m.cr = lds32(a + 2048); m.ci = lds32(a + 3072);
  const uint32_t o0 = lds32((a ^ 128) + 2048), o1 = lds32((a ^ 128) + 3072), ld = lds16(b), dsk = lds16(b + 16);
  const uint32_t m2 = __vmaxu2(__vmaxu2(m.cr & 0x7fff7fffu, m.ci & 0x7fff7fffu), __vmaxu2(o0 & 0x7fff7fffu, o1 & 0x7fff7fffu));
  m.e = min(max(__reduce_max_sync(0xffffffffu, max(m2 & 0xffffu, m2 >> 16)) >> 7, 1u), 253u) << 23 | dsk;
  m.dt = bf_round(expf(bf_lo(ld)));
  return m;
}
struct Powers { uint32_t re[3][4], im[3][4]; cf z4; };
__device__ __forceinline__ void powers(const Modes& m, Powers& g) {
  const float la2 = -bf_round(expf(bf_lo(m.la))) * m.dt * 1.4426950408889634f;
  const float beta = bf_lo(m.ai) * m.dt;
  const cf z1 = cpow_seed(la2, beta, 1.f), z2 = csq(z1), z3 = cmul(z2, z1), z4 = csq(z2), z5 = cmul(z4, z1), z6 = csq(z3), z7 = cmul(z4, z3);
  g.z4 = z4;
  g.re[0][0] = pack_f16(1.f, z4.r); g.re[0][1] = pack_f16(z2.r, z6.r); g.re[0][2] = pack_f16(z1.r, z5.r); g.re[0][3] = pack_f16(z3.r, z7.r);
  g.im[0][0] = pack_f16(0.f, z4.i); g.im[0][1] = pack_f16(z2.i, z6.i); g.im[0][2] = pack_f16(z1.i, z5.i); g.im[0][3] = pack_f16(z3.i, z7.i);
  const cf v1 = cpow_seed(la2, beta, 256.f), v2 = csq(v1), v3 = cmul(v2, v1), v4 = csq(v2), v5 = cmul(v4, v1), v6 = csq(v3), v7 = cmul(v4, v3), v8 = csq(v4);
  const uint32_t p1 = pack_f16(v1.r, v1.i);
  hcmul(g.re[0][0], g.im[0][0], p1, g.re[1][0], g.im[1][0]);
  hcmul(g.re[0][1], g.im[0][1], p1, g.re[1][1], g.im[1][1]);
  hcmul(g.re[0][0], g.im[0][0], pack_f16(v2.r, v2.i), g.re[1][2], g.im[1][2]);
  hcmul(g.re[0][0], g.im[0][0], pack_f16(v3.r, v3.i), g.re[1][3], g.im[1][3]);
  g.re[2][0] = pack_f16(v4.r, v5.r); g.re[2][1] = pack_f16(v6.r, v7.r); g.re[2][2] = g.re[2][3] = pack_f16(v8.r, 0.f);
  g.im[2][0] = pack_f16(v4.i, v5.i); g.im[2][1] = pack_f16(v6.i, v7.i); g.im[2][2] = g.im[2][3] = pack_f16(v8.i, 0.f);
}
__device__ __forceinline__ void kgen_operands(const Modes& m, const Powers& g, uint32_t buf, int chi, int mu) {
  const uint32_t sa = buf + chi * 8192 + mu * 16, sbb = buf + 16384 + chi * 6144 + mu * 16;
  auto store_b = [&](int q) {
    sts128(sbb + 2048 * q, g.re[q][0], g.re[q][1], g.re[q][2], g.re[q][3]);
    sts128(sbb + 2048 * q + 1024, g.im[q][0], g.im[q][1], g.im[q][2], g.im[q][3]);
  };
  store_b(0);
  cf w8 = csq({g.z4.r, -g.z4.i}), w16 = csq(w8);
  const float psd = __uint_as_float((254u << 23) - (m.e & 0xffff0000u));
  const cf a0 = {bf_lo(m.cr) * psd, -bf_lo(m.ci) * psd};
  asm volatile("" : "+f"(w16.r), "+f"(w16.i)::"memory");
  store_b(1);
  const cf a1 = cmul(a0, w8), a2 = cmul(a0, w16), a3 = cmul(a1, w16);
  cf w32 = csq(w16), w64 = csq(w32);
  uint32_t R[4], I[4], r[4], i[4];
  R[0] = pack_f16(a0.r, a1.r); R[1] = pack_f16(a2.r, a3.r);
  I[0] = pack_f16(a0.i, a1.i); I[1] = pack_f16(a2.i, a3.i);
  asm volatile("" : "+f"(w64.r), "+f"(w64.i)::"memory");
  store_b(2);
  const cf w128 = csq(w64), w192 = cmul(w64, w128);
  const uint32_t w[4] = {pack_f16(w32.r, w32.i), pack_f16(w64.r, w64.i), pack_f16(w128.r, w128.i), pack_f16(w192.r, w192.i)};
  hcmul(R[0], I[0], w[0], R[2], I[2]); hcmul(R[1], I[1], w[0], R[3], I[3]);
  sts128(sa, R[0], R[1], R[2], R[3]); sts128(sa + 1024, I[0], I[1], I[2], I[3]);
#pragma unroll
  for (int q = 1; q < 4; q++) {
#pragma unroll
    for (int k = 0; k < 4; k++) hcmul(R[k], I[k], w[q], r[k], i[k]);
    sts128(sa + 2048 * q, r[0], r[1], r[2], r[3]); sts128(sa + 2048 * q + 1024, i[0], i[1], i[2], i[3]);
  }
  fence_async_smem();
}
__device__ __forceinline__ void kgen_mma(float (&dk)[24], uint32_t buf, int scale) {
  const uint32_t da = (buf >> 4) | (64u << 16), db = da + 1024;
  wg_fence();
#pragma unroll
  for (int k = 0; k < 8; k++) mma_kgen(dk, da + 8 * k, db + 8 * k, scale | k);
  wg_commit();
}
__device__ __forceinline__ void kgen_dump(const float (&dk)[24], float pks, float skip, uint32_t kc, uint32_t s0, int w4, int lane) {
  const int chi = w4 >> 1, g = lane >> 2, t = lane & 3, mu = 32 * (w4 & 1) + lane;
  const int i0 = 16 * (w4 & 1) + g;
  float v[12];
  if (chi) {
#pragma unroll
    for (int k = 0; k < 12; k++) asm volatile("mul.rn.f32 %0, %1, %2;" : "=f"(v[k]) : "f"(dk[12 + k]), "f"(pks));
  } else {
#pragma unroll
    for (int k = 0; k < 12; k++) v[k] = dk[k] * pks;
  }
  if (mu == 0) v[0] += skip;
  const uint32_t b = kc + 4 * (t < 2 ? 4 + 4 * i0 + t : 4 + 64 * t + 2 * i0);
  const uint32_t be = t < 2 ? 8 : 4;
  stsf(b, v[4]); stsf(b + be, v[5]); stsf(b + 16 * be, v[6]); stsf(b + 17 * be, v[7]);
  const uint32_t c = kc + 4 * (260 + 64 * t + i0);
  if (t < 2) { stsf(c, v[8]); stsf(c + 128, v[9]); stsf(c + 32, v[10]); stsf(c + 160, v[11]); }
  else if (t == 2 && i0 == 0) stsf(c, v[8]);
  else if (mu == 63) stsf(kc + 12, v[3]);
  const uint32_t a = s0 + 16 * i0 + 2 * ((t & 1) * 2 + (t >> 1));
  const uint32_t e0 = pack_bf16(v[0], v[1]), e1 = pack_bf16(v[2], v[3]);
  sts16(a, e0); sts16(a + 8, e0 >> 16); sts16(a + 128, e1); sts16(a + 136, e1 >> 16);
  sts16(a + KT_COPY + 2, e0); sts16(a + KT_COPY + 10, e0 >> 16); sts16(a + KT_COPY + 130, e1);
  if (mu != 63) sts16(a + KT_COPY + 138, e1 >> 16);
  if (mu < 14) sts128(s0 - 112 + 16 * mu + (mu < 7 ? 0 : KT_COPY - 112), 0, 0, 0, 0);
  else if (mu == 14) sts16(s0 + KT_COPY, 0);
}
template <bool LEAN> __device__ __forceinline__ void kgen_expand(uint32_t kc, uint32_t s0, int w4, int lane) {
  const int mu = 32 * (w4 & 1) + lane;
  const bool odd = w4 & 1;
  const float4 a = ldsf4(kc + 16 + 16 * lane);
  float ax = ldsf(odd ? kc + 12 : kc + 32 + 16 * lane);
  float2 q;
  float q2, r[4];
  auto load_q = [&]() { q = ldsf2(kc + 528 + 8 * mu); q2 = ldsf(kc + 536 + 8 * mu); };
  auto load_r = [&](int k) { r[2 * k] = ldsf(kc + 1040 + 256 * k + 4 * mu); r[2 * k + 1] = ldsf(kc + 1044 + 256 * k + 4 * mu); };
  if (!LEAN) { load_q(); load_r(0); load_r(1); }
  {
    const uint32_t c22 = pack_bf16(a.z, a.z);
    if (!odd) sts128(s0 + 512 + 16 * lane, pack_bf16(a.x, a.x), pack_bf16(a.y, a.z), c22, pack_bf16(a.w, ax));
    else sts128(s0 + KT_COPY + 512 + 16 * lane, pack_bf16(lane ? a.x : ax, a.x), pack_bf16(a.x, a.y), c22, pack_bf16(a.z, a.w));
  }
  if (LEAN) { load_q(); load_r(0); }
  const uint32_t sm0 = s0 + 16 * mu, sm1 = sm0 + KT_COPY;
  {
    const uint32_t c00 = pack_bf16(q.x, q.x), c11 = pack_bf16(q.y, q.y);
    sts128(sm0 + 1024, c00, pack_bf16(q.x, q.y), c11, pack_bf16(q2, q2));
    sts128(sm1 + 1024, c00, c00, c11, pack_bf16(q.y, q2));
  }
  if (LEAN) load_r(1);
#pragma unroll
  for (int k = 0; k < 2; k++) {
    const float pa = r[2 * k], pb = r[2 * k + 1], px = (lane & 1) ? pb : pa;
    const uint32_t caa = pack_bf16(pa, pa), cbb = pack_bf16(pb, pb);
    sts128(sm0 + 2048 + 1024 * k, caa, caa, pack_bf16(px, pb), cbb);
    sts128(sm1 + 2048 + 1024 * k, caa, caa, pack_bf16(pa, px), cbb);
  }
  fence_async_smem();
}

template <int I, int E> struct ConvSeq {
  static __device__ __forceinline__ void run(float (&d)[64], uint32_t a, uint32_t b) {
    constexpr int J = I >> 1, S = I & 1;
    mma_conv<128 - 8 * J>(d, a + S * (KT_COPY / 16) + 16 * J, b + S * (UT_PAR / 16) + 8 * J, I != 0);
    ConvSeq<I + 1, E>::run(d, a, b);
  }
};
template <int E> struct ConvSeq<E, E> { static __device__ __forceinline__ void run(float (&)[64], uint32_t, uint32_t) {} };

struct Params {
  const __nv_bfloat16* first[3];
  const __nv_bfloat16 *log_a, *a_im, *c_re, *c_im, *log_dt, *d_skip, *gate_w, *w_down, *x, *w_gate, *w_up;
};

enum { TM_X, TM_WG, TM_WG3, TM_WU, TM_WU3, TM_WD, TM_OUT, TM_U, TM_XP, TM_UL, TM_WGX, TM_WUX, TM_COUNT };
struct Maps { CUtensorMap m[TM_COUNT]; };

__device__ __forceinline__ void extra_cta(const Params& p, const Maps& tm) {
  constexpr uint32_t sd = 1024, OFF_X = 98304, B_F = OFF_BAR, B_W = OFF_BAR + 128;
  const uint32_t sb = sd + ((blockIdx.x & 1) << 24);
  const int warp = __shfl_sync(0xffffffffu, threadIdx.x >> 5, 0), lane = threadIdx.x & 31, wg = warp >> 2;
  const int row0 = 512 * (blockIdx.x - 128), k = threadIdx.x;
  auto x_load = [&](int ks) {
    const uint32_t bar = sb + B_F + 32 * wg + 8 * (ks & 3);
    mbar_expect(bar, 8192);
    tma2d(sb + OFF_X + 32768 * wg + 8192 * (ks & 3), tm.m + TM_X, bar, 32 * ks, row0 + 128 * wg);
  };
  auto w_load = [&](int q) {
    const uint32_t bar = sb + B_W + 8 * q;
    mbar_expect(bar, 8192);
    tma2d(sb + 4096 * q, tm.m + TM_WGX, bar, 1344, 64 * q);
    tma2d(sb + 32768 + 4096 * q, tm.m + TM_WUX, bar, 1344, 64 * q);
  };
  const uint32_t gw = __ldg((const uint32_t*)p.gate_w + (k & 255));
  if (!(k & 127)) {
#pragma unroll
    for (int i = 0; i < 4; i++) mbar_init(sb + B_F + 32 * wg + 8 * i, 1);
    mbar_init(sb + B_W + 8 * wg, 1); mbar_init(sb + B_W + 8 * wg + 32, 1);
    fence_async_smem();
    if (wg == 0) w_load(0);
#pragma unroll 1
    for (int ks = 0; ks < 4; ks++) { x_load(ks); if (ks == 1 && wg) w_load(wg); }
  }
  if (k < 304) sts32(sb + 65536 + 4 * k, k < 256 ? gw : (k & 16) ? 0x3f803f80u : 0u);
  fence_async_smem();
  __syncthreads();
  float d0[32], d1[32], lg[4];
  const int ar = 16 * (warp & 3) + (lane & 15);
  const uint32_t xa = sb + OFF_X + 32768 * wg + ar * 64 + 16 * ((lane >> 4) ^ ((ar >> 1) & 3));
  uint32_t a0[10], a1[10];
  auto fetch = [&](uint32_t (&a)[10], int kk) {
    const uint32_t src = (xa + 8192 * ((kk >> 1) & 3)) ^ (32 * (kk & 1));
    ldsm4(src, a);
    ldsm4(src + 4096, a + 4);
    a[8] = lds32(sb + 65536 + 32 * kk + 4 * (lane & 3));
    a[9] = lds32(sb + 65552 + 32 * kk + 4 * (lane & 3));
  };
  auto step = [&](uint32_t (&a)[10], int kk) {
    uint32_t q[8];
#pragma unroll
    for (int i = 0; i < 8; i++) q[i] = bmul2(a[i], a[8 + ((i >> 1) & 1)]);
    const uint32_t db = ((sd >> 4) + 64 * kk) | (2048u << 16);
    constexpr uint32_t ones = (sd + 66560) >> 4;
    wg_fence();
    mma_sum(lg, q, ones + 4, kk);
    mma_x(d0, a, db, kk);
    mma_sum(lg, q + 4, ones, 1);
    mma_x(d1, a + 4, db, kk);
    wg_commit();
  };
  mbar_wait(sb + B_F + 32 * wg, 0);
  fetch(a0, 0);
#pragma unroll 1
  for (int ks = 0; ks < 16; ks++) {
    if (!(ks & 1)) mbar_wait(sb + B_W + 4 * ks, 0);
    step(a0, 2 * ks);
    fetch(a1, 2 * ks + 1);
    wg_wait<0>();
    step(a1, 2 * ks + 1);
    const int kn = min(ks + 1, 15);
    mbar_wait(sb + B_F + 32 * wg + 8 * (kn & 3), (kn >> 2) & 1);
    fetch(a0, 2 * kn);
    nb_sync(1 + wg, 128);
    if (!(k & 127)) {
      if (ks < 12) x_load(ks + 4);
      if (ks == 2 * wg + 1) w_load(4 + wg);
    }
    __syncwarp();
    wg_wait<0>();
  }
  pin(d0); pin(d1); pin(lg);
  uint8_t* hp = g_h + ((size_t)(row0 / 64 + 2 * (warp >> 2)) * 88 + 84) * 2048 + (warp & 3) * 256 + lane * 4;
#pragma unroll
  for (int e = 0; e < 8; e++) {
    *(uint32_t*)(hp + (e >> 1) * 1024 + (e & 1) * 128) = pack_bf16(swiglu(d0[2 * e], d0[16 + 2 * e]), swiglu(d0[2 * e + 1], d0[17 + 2 * e]));
    *(uint32_t*)(hp + 88 * 2048 + (e >> 1) * 1024 + (e & 1) * 128) = pack_bf16(swiglu(d1[2 * e], d1[16 + 2 * e]), swiglu(d1[2 * e + 1], d1[17 + 2 * e]));
  }
  {
    const float logit = (lane & 1) ? lg[2] : lg[0];
    const float gt = bf_round(1.f / (1.f + expf(-bf_round(logit))));
    g_gate[row0 + 128 * wg + 32 * (lane & 2) + 16 * (warp & 3) + 8 * (lane & 1) + (lane >> 2)] = pack_bf16(gt, 1.f - gt);
  }
  __syncthreads();
  if (k == 0) asm volatile("red.release.gpu.global.add.u32 [%0], 32;" ::"l"(g_flags + (FL_X + blockIdx.x - 128) * FLAG_STRIDE) : "memory");
}

}

__global__ void __cluster_dims__(2, 1, 1) __launch_bounds__(512, 1)
gated_mix_kernel(const __grid_constant__ Params p, const __grid_constant__ Maps tm) {
  extern __shared__ uint8_t smem_raw[];
  constexpr uint32_t sd = 1024;
  if (threadIdx.x < 96) {
    const uint32_t kind = threadIdx.x >> 5, k = threadIdx.x & 31;
    const uint32_t off = ((kind ? 22 : 32) * (blockIdx.x & 63) + min(k, kind ? 21u : 31u)) << (kind ? 7 : 10);
    asm volatile("prefetch.global.L2 [%0];" ::"l"((const uint8_t*)p.first[kind] + off) : "memory");
  }
  if (blockIdx.x >= 128) { extra_cta(p, tm); return; }
  const int rank = blockIdx.x & 1, cl = blockIdx.x >> 1;
  const uint32_t sb = sd + ((uint32_t)rank << 24);
  if (threadIdx.x == 416) {
    init_barriers<0, 12>(sb + OFF_BAR);
    asm volatile("fence.mbarrier_init.release.cluster;" ::: "memory");
    fence_async_smem();
  }
  if (threadIdx.x == 384) {
    asm volatile("prefetch.tensormap [%0];" ::"l"(tm.m + TM_WG + 2 * rank) : "memory");
    asm volatile("prefetch.tensormap [%0];" ::"l"(tm.m + TM_WG3 + 2 * rank) : "memory");
    asm volatile("prefetch.tensormap [%0];" ::"l"(tm.m + TM_X) : "memory");
  }
  __syncwarp();
  asm volatile("barrier.cluster.arrive.relaxed.aligned;" ::: "memory");
  const int warp = __shfl_sync(0xffffffffu, threadIdx.x >> 5, 0);
  const int lane = threadIdx.x & 31;
  const int wg = warp >> 2, w4 = warp & 3;
  const int row7 = ((cl - 36) * 37) >> 8;
  const int ia = 8 + 2 * cl, ib = 16 * ((cl - 4) & 7) + 2 * ((cl - 4) >> 3), ic = 16 * cl - 552 - 110 * row7;
  const int cta = rank + selp(ia, selp(ib, ic, cl < 36), cl < 4);
  const int mb = 2 * (cta >> 4) + rank;
  const int nb = (cta >> 1) & 7;
  const int m2 = cta >> 3;
  const int tb = 2 * m2 + rank;
  const int cq = (cta >> 1) & 3;

  auto g1_load = [&](int ks, uint32_t slot) {
    const uint32_t bar = sb + B_FULL1 + 8 * slot, dst = sb + slot * SLOT1;
    mbar_expect(bar, 8192 + 2 * (8192 + 2560));
    tma3d_pair(dst + 8192 + 12288 * rank, tm.m + TM_WG + 2 * rank, bar, 64 * nb, 32 * ks, 0);
    tma2d_pair(dst + 16384 + 12288 * rank, tm.m + TM_WG3 + 2 * rank, bar, 1024 + 40 * nb, 32 * ks);
    tma2d(dst, tm.m + TM_X, bar, 32 * ks, 128 * mb);
  };

  if (wg == 2) {
    asm volatile("setmaxnreg.dec.sync.aligned.u32 88;");
    const int tau = threadIdx.x & 127, chi = w4 >> 1, mu = tau & 63;

    const uint32_t kc = sb + OFF_PARK + chi * KC_CH;
    {
      const int o = 1024 * cta + 16 * mu;
      cp_async16(sb + OFF_PARK + 16 * tau, (const uint8_t*)(w4 < 2 ? p.log_a : p.a_im) + o);
      cp_async16(sb + OFF_PARK + 2048 + 16 * tau, (const uint8_t*)(w4 < 2 ? p.c_re : p.c_im) + o);
      if (!(tau & 63)) cp_async16(sb + OFF_PARK + 4224 + 8 * w4, (const uint8_t*)(w4 ? p.d_skip : p.log_dt) + 16 * (cta >> 1));
    }
    asm volatile("cp.async.wait_all;" ::: "memory");
    nb_sync(NB_PAR, 224);
    Modes m = load_modes(sb + OFF_PARK, conv_ch(chi), cta & 1, mu);
    Powers pw;
    powers(m, pw);
    float dk[24];
#pragma unroll 1
    for (int it = 0; it < 4; it++) {
      kgen_operands(m, pw, sb + OFF_KS, chi, mu);
      nb_sync(NB_AUX, 128);
      int tid_local = threadIdx.x;
      asm volatile("" : "+r"(tid_local), "+r"(m.e));
      const int lane = tid_local & 31, mu = tid_local & 63;
      kgen_mma(dk, sd + OFF_KS, it & 1);
      float pks = 2.f * m.dt * bf_hi(m.e), skip = bf_lo(m.e);
      asm volatile("" : "+f"(pks), "+f"(skip));
      if (it == 1) {
        m = load_modes(sb + OFF_PARK, conv_ch(2 + chi), cta & 1, mu);
      } else {
        m.la >>= 16; m.ai >>= 16; m.cr >>= 16; m.ci >>= 16;
      }
      if (it < 3) powers(m, pw);
      wg_wait<0>();
      pin(dk);
      nb_sync(NB_AUX, 128);
      if (it & 1) mbar_wait(sb + (it == 1 ? B_XTREAD : B_TAB), 0);
      if (it & 1) kgen_dump(dk, pks, skip, kc, sb + (it == 1 ? OFF_A : OFF_KT23) + chi * KT_CH + 112, w4, lane);
      if (it == 1) { fence_async_smem(); nb_arrive(NB_KC0, 192); }
    }
    nb_sync(NB_AUX, 128);
    kgen_expand<false>(kc, sb + OFF_KT23 + chi * KT_CH + 112, w4, lane);
    __syncwarp();
    if (lane == 0) mbar_arrive(sb + B_TAB + 8);

    {
      const int half = lane >> 4, wd = 16 * (w4 & 1) + (lane & 15), row0 = 16 * (w4 >> 1) + half;
      uint32_t pa[4];
#pragma unroll
      for (int r = 0; r < 4; r++) {
        const int sw = (wd - r) & 31, row = row0 - (wd < r);
        pa[r] = sb + OFF_P + r * 4096 + row * 128 + 16 * ((sw >> 2) ^ r ^ (4 * (row & 1))) + 4 * (sw & 3);
      }
#pragma unroll 1
      for (int c = 0; c < 4; c++) {
        const int ch = 4 * cta + conv_ch(c);
        uint8_t* yo = g_y + ((size_t)row0 * 512 + ch) * 128 + 16 * ((wd >> 2) ^ (ch & 7)) + 4 * (wd & 3);
        nb_sync(NB_PFULL0 + (c & 1), 256);
        uint32_t o[8];
        const uint32_t pb = (c & 1) ? 0 : OFF_RECV;
#pragma unroll
        for (int k = 0; k < 8; k++) {
          uint32_t v0 = lds32(pa[0] + pb + 256 * k), v1 = lds32(pa[1] + pb + 256 * k), v2 = lds32(pa[2] + pb + 256 * k), v3 = lds32(pa[3] + pb + 256 * k);
          if (k == 0 && row0 == 0) { if (wd < 1) v1 = 0; if (wd < 2) v2 = 0; if (wd < 3) v3 = 0; }
          o[k] = badd2(badd2(v0, v1), badd2(v2, v3));
        }
#pragma unroll
        for (int k = 0; k < 8; k++) *(uint32_t*)(yo + (size_t)k * 131072) = o[k];
        __syncwarp();
        if (lane == 0) mbar_arrive(sb + B_PEMPTY + 8 * c);
      }
      nb_sync(NB_AUX, 128);
      if (tau == 0) flag_signal(FL_Y + (cta >> 5), 1);
      __syncwarp();
    }
    if (lane == 0) mbar_arrive(sb + B_DONE);
    return;
  }

  if (warp == 12) {
    cluster_wait();
    if (elect()) g1_load(0, 0);
    __syncwarp();
  }

  if (wg == 1 && w4 < 3) {
    if (elect()) {
      if (w4 == 0) init_barriers<12, 26>(sb + OFF_BAR);
      else if (w4 == 1) init_barriers<26, 40>(sb + OFF_BAR);
      else init_barriers<40, 56>(sb + OFF_BAR);
      fence_async_smem();
    }
    __syncwarp();
    nb_arrive(NB_INIT, 192);
    nb_arrive(NB_PAR, 224);
  }

  if (wg == 3) {
    asm volatile("setmaxnreg.dec.sync.aligned.u32 24;");
    if (w4) { cluster_wait(); nb_sync(NB_INIT, 192); }
    auto h_publish = [&](int w) {
      uint32_t* f = g_flags + (FL_H + 2 * mb + w) * FLAG_STRIDE;
      asm volatile("" : "+l"(f));
      nb_sync(NB_H0 + w, 160);
      if (elect()) asm volatile("red.release.gpu.global.add.u32 [%0], 4;" ::"l"(f) : "memory");
      __syncwarp();
    };
    const uint8_t* hsrc = g_h + ((size_t)2 * m2 * 88 + 43 * rank) * 2048;
    if (w4 >= 2) {
      const int ii = lane & 7;
      const uint32_t src = sb + OFF_A + (64 * (w4 & 1) + 7 - ii) * 128 + 16 * ((lane >> 3) ^ (7 - ii));
      const uint32_t dst = sb + OFF_UT + lane * 128 + 16 * ((4 * (1 - (w4 & 1))) ^ ii);
      mbar_wait(sb + B_XTFULL, 0);
#pragma unroll 1
      for (int r = 0; r < 8; r++) {
        uint32_t v[8];
        ldsm4(src + r * 1024, v);
        ldsm4((src + r * 1024) ^ 64, v + 4);
        const uint32_t o = (dst + (r & 1) * 8192) ^ (8 * (r & 6));
        stsm4t(o, v[0], v[1], v[2], v[3]);
        stsm4t(o + 4096, v[4], v[5], v[6], v[7]);
      }
      fence_async_smem();
      nb_arrive(NB_UT, 96);
      nb_sync(NB_KC0, 192);
#pragma unroll 1
      for (int half = 0; half < 2; half++) {
        kgen_expand<true>(sb + OFF_PARK + (w4 & 1) * KC_CH, sb + OFF_A + (w4 & 1) * KT_CH + 112, half, lane);
        __syncwarp();
        if (lane == 0) mbar_arrive(sb + B_TAB);
      }
    }
    if (w4 == 0) {
      if ((uint32_t)__cvta_generic_to_shared(smem_raw) != sb) __trap();
      uint32_t slot = 1, ph = 1;
#pragma unroll 1
      for (int ks = 1; ks < 16; ks++) {
        mbar_wait(sb + B_EMPTY1 + 8 * slot, ph);
        if (elect()) g1_load(ks, slot);
        __syncwarp();
        if (++slot == 5) { slot = 0; ph ^= 1; }
      }
      if (elect()) mbar_expect(sb + B_WF, 5 * 16384);
#pragma unroll 1
      for (int q = 0; q < 11; q++) {
        const int st = q < 4 ? q + 1 : q == 4 ? 0 : q;
        slot = st < 6 ? st : st - 6;
        mbar_wait(sb + (q < 4 ? B_EMPTY1 + 8 + 8 * (q >> 1) : q == 4 ? B_G1DONE : q == 5 ? B_PEMPTY + 16 : B_EMPTYW + 8 * slot), 0);
        if (elect()) {
          const uint32_t bar = sb + (st < 5 ? B_WF : st == 5 ? B_W5 : B_FULL3 + 8 * slot);
          if (st >= 5) mbar_expect(bar, 16384);
          tma3d(sb + OFF_W2 + 16384 * slot, tm.m + TM_WD, bar, 0, 688 * rank + 64 * st, 2 * cq);
          if (st == 10) mbar_wait(sb + B_XOK, 0);
          if (st >= 6) bulk_load(sb + OFF_A + 8192 * slot, hsrc + rank * (88 * 2048) + st * 8192, st == 10 ? 6144 : 8192, sb + B_KH);
        }
        __syncwarp();
      }
    } else if (w4 == 1) {
      uint32_t target;
      asm volatile("ld.relaxed.gpu.global.u32 %0, [%1];" : "=r"(target) : "l"(g_flags + (FL_U + nb) * FLAG_STRIDE) : "memory");
      target = (target & ~31u) + 32;
      if (elect()) {
        sts32(sb + OFF_EPOCH, target);
        mbar_expect(sb + B_XTFULL, 16384);
        tma4d(sb + OFF_A, tm.m + TM_XP, sb + B_XTFULL, 64 * nb, 0, 0, 2 * mb);
#pragma unroll
        for (int i = 0; i < 5; i++) if (i != 3) asm volatile("prefetch.tensormap [%0];" ::"l"(tm.m + TM_WD + i) : "memory");
      }
      __syncwarp();
      nb_sync(NB_UT, 96);
      if (elect()) {
        mbar_arrive(sb + B_XTREAD);
        tma3d_store(tm.m + TM_U, sb + OFF_UT, 32 * (30 - 2 * mb), 64 * nb, 0);
        asm volatile("cp.async.bulk.commit_group;" ::: "memory");
        asm volatile("cp.async.bulk.wait_group 0;" ::: "memory");
      }
      __syncwarp();
      if (elect()) {
        flag_signal(FL_U + nb, 2);
        asm volatile("cp.async.bulk.prefetch.L2.global [%0], %1;" ::"l"((const uint8_t*)p.w_down + (size_t)cta * 11008), "r"(11008) : "memory");
        mbar_expect(sb + B_UFULL, 4 * UT_CH);
        flag_wait(FL_U + (cta >> 4), target);
        tma4d(sb + OFF_UT, tm.m + TM_UL, sb + B_UFULL, 0, 0, 0, 4 * cta);
        mbar_expect(sb + B_RECV, 16384);
      }
      __syncwarp();
      mbar_wait(sb + B_G1DONE, 0);
      if (elect()) {
#pragma unroll 1
        for (int s = 0; s < 6; s++) mbar_expect(sb + B_HE + 8 * s, 8192);
        flag_wait(FL_H + 2 * m2, target);
#pragma unroll
        for (int s = 0; s < 6; s++) bulk_load(sb + OFF_HE + 8192 * s, hsrc + s * 8192, 8192, sb + B_HE + 8 * s);
        if (rank == 0) flag_wait(FL_H + 2 * m2 + 1, target);
#pragma unroll 1
        for (int s = 0; s < 5; s++) {
          const uint32_t bytes = s == 4 ? 6144 : 8192;
          mbar_expect(sb + B_FULL3 + 8 * s, bytes);
          if (s == 4) mbar_wait(sb + B_XOK, 0);
          mbar_wait(sb + B_EMPTYH + 8 * s, 0);
          bulk_load(sb + OFF_HE + 8192 * s, hsrc + (rank ^ 1) * (88 * 2048) + 49152 + s * 8192, bytes, sb + B_FULL3 + 8 * s);
        }
      }
      __syncwarp();
    } else if (w4 == 2) {
      h_publish(0);
      mbar_wait(sb + B_PEMPTY + 24, 0);
      if (elect()) {
        mbar_expect(sb + B_YFULL, 16384);
        flag_wait(FL_Y + cq, lds32(sb + OFF_EPOCH));
        bulk_load(sb + OFF_P, g_y + ((size_t)tb * 512 + 128 * cq) * 128, 16384, sb + B_YFULL);
      }
      __syncwarp();
    } else {
      if (elect()) {
#pragma unroll 1
        for (int s = 0; s < 6; s++) mbar_expect(sb + B_HL + 8 * s, 8192);
        mbar_expect(sb + B_KH, 38912 + 256);
      }
      __syncwarp();
      const uint32_t target = lds32(sb + OFF_EPOCH);
      h_publish(1);
      if (elect()) {
        flag_wait(FL_H + 2 * m2 + 1, target);
        mbar_wait(sb + B_C12, 0);
#pragma unroll
        for (int s = 0; s < 6; s++) bulk_load(sb + (s < 5 ? OFF_A + 8192 * s : OFF_HL5), hsrc + 88 * 2048 + s * 8192, 8192, sb + B_HL + 8 * s);
        flag_wait(FL_X + (m2 >> 2), target);
        mbar_arrive(sb + B_XOK);
        bulk_load(sb + OFF_GATE, g_gate + 64 * tb, 256, sb + B_KH);
      }
      __syncwarp();
      mbar_wait(sb + B_DONE, 0);
      return;
    }
    if (lane == 0) mbar_arrive(sb + B_DONE);
  } else {
    nb_sync(NB_SKEW, 256);
    asm volatile("setmaxnreg.inc.sync.aligned.u32 200;");
    cluster_wait();
    {
      float ag[84], au[84];
      const uint32_t da0 = ((sd >> 4) + wg * 256) | (1u << 16);
      constexpr uint32_t db0 = ((sd >> 4) + 512) | (256u << 16);
      const uint32_t rel = sd + B_EMPTY1 + (lane << 24);
      auto release = [&](int slot) { if (lane < 2) mbar_arrive_cluster(rel + 8 * slot); };
      auto g1_stage = [&](int slot, uint32_t ph, int scale) {
        mbar_wait(sb + B_FULL1 + 8 * slot, ph);
        const uint32_t da = da0 + slot * (SLOT1 / 16), db = db0 + slot * (SLOT1 / 16);
        wg_fence();
        mma_g1(ag, da, db, scale);
        mma_g1(au, da, db + 768, scale);
        wg_commit();
        mma_g1(ag, da + 2, db + 128, 1);
        mma_g1(au, da + 2, db + 768 + 128, 1);
        wg_commit();
      };
#pragma unroll 1
      for (int it = 0; it < 2; it++) {
#pragma unroll
        for (int q = 0; q < 5; q++) {
          g1_stage(q, it, it | q);
          wg_wait<2>();
          if (q || it) release((q + 4) % 5);
          wg_wait<1>();
        }
      }
#pragma unroll
      for (int q = 0; q < 6; q++) {
        if (q == kSkewAt && wg == 1) { wg_wait<0>(); release(q - 1); nb_sync(NB_SKEW, 256); }
        g1_stage(q % 5, q / 5, 1);
        if (q == 5) nb_arrive(wg ? NB_GO0 : NB_SKEW, 256);
        if (q < 5) {
          wg_wait<2>();
          if (!(q == kSkewAt && wg == 1)) release((q + 4) % 5);
          if (q < kSkewAt - 1) wg_wait<1>();
        }
      }
      wg_wait<0>();
      pin(ag); pin(au);
      if (lane == 0) mbar_arrive(sb + B_G1DONE);
      uint8_t* hp = g_h + (size_t)(2 * mb + wg) * 88 * 2048 + nb * 8192 + w4 * 256 + lane * 4;
      float th[84];
      auto lead = [&](int j) {
#pragma unroll
        for (int e = 4 * j; e < 4 * j + 4; e++) {
          ag[e] *= 0.5f;
          asm("tanh.approx.f32 %0, %1;" : "=f"(th[e]) : "f"(ag[e]));
        }
      };
      auto trail = [&](int j) {
        if (j == 16) hp -= nb * 3072;
#pragma unroll
        for (int e = 0; e < 2; e++) {
          const float q0 = ag[4 * j + 2 * e] * au[4 * j + 2 * e], q1 = ag[4 * j + 2 * e + 1] * au[4 * j + 2 * e + 1];
          *(uint32_t*)(hp + (j >> 3) * 65536 + (j & 7) * 1024 + e * 128) =
              pack_bf16(fmaf(q0, th[4 * j + 2 * e], q0), fmaf(q1, th[4 * j + 2 * e + 1], q1));
        }
      };
#pragma unroll
      for (int j = 0; j < 2; j++) lead(j);
#pragma unroll
      for (int j = 0; j < 21; j++) {
        trail(j);
        if (j + 2 < 21) lead(j + 2);
        if (j & 1) {
#pragma unroll
          for (int e = 4 * (j + 1); e < 4 * (j + 3) && e < 84; e++) asm volatile("" : "+f"(th[e]));
          if (j == 13) { mbar_wait(sb + B_TAB, 0); mbar_wait(sb + B_UFULL, 0); }
          else sched_fence(gridDim.x, j);
        }
      }
      nb_arrive(NB_H0 + wg, 160);
    }
    const int mat = lane >> 3, ii = lane & 7;
    {
      uint32_t pw = sb + (wg ? OFF_P : OFF_RECV) + (ii & 3) * 4096 + (31 - 2 * (mat >> 1) - (ii >> 2)) * 128 +
                    16 * ((2 * w4 + (mat & 1)) ^ (ii & 3) ^ (4 * (1 - (ii >> 2))));
      uint32_t da = ((sd + OFF_A + wg * KT_CH) >> 4) | (8u << 16), db = ((sd + OFF_UT + conv_ch(wg) * UT_CH) >> 4) | (4u << 16);
#pragma unroll 1
      for (int r = 0; r < 2; r++) {
        nb_sync(NB_GO0 + wg, 256);
        float d[64];
        wg_fence();
        ConvSeq<0, kConvHead>::run(d, da, db);
        nb_sync_if(r | wg, NB_ST0 + wg, 256);
        ConvSeq<kConvHead, 32>::run(d, da, db);
        wg_commit();
        nb_arrive(NB_GO0 + (wg ^ 1), 256);
        mbar_wait(sb + (r ? B_PEMPTY + 8 * wg : B_G1DONE), 0);
        wg_wait<0>();
        pin(d);
        if (r != wg && lane == 0) mbar_arrive(sb + B_C12);
#pragma unroll
        for (int q = 0; q < 8; q++)
          stsm4t(pw - 512 * q, pack_bf16(d[8 * q], d[8 * q + 1]), pack_bf16(d[8 * q + 2], d[8 * q + 3]),
                 pack_bf16(d[8 * q + 4], d[8 * q + 5]), pack_bf16(d[8 * q + 6], d[8 * q + 7]));
        nb_arrive(NB_PFULL0 + wg, 256);
        nb_arrive(NB_ST0 + (wg ^ 1), 256);
        if (!r) mbar_wait(sb + B_TAB + 8, 0);
        da += (OFF_KT23 - OFF_A) / 16;
        db += wg ? -(int)(2 * UT_CH / 16) : (int)(2 * UT_CH / 16);
      }
    }
    const bool keeper = wg == rank;
    const uint32_t peer = sb ^ (1u << 24);
    float d[64];
    auto g2_stage = [&](uint32_t da, int slot, int nk, int scale) {
      const uint32_t db = ((sd + OFF_W2 + 16384 * slot) >> 4) | (512u << 16);
      wg_fence();
#pragma unroll
      for (int k = 0; k < nk; k++) {
        mma_g2(d, da + 128 * k, db + 128 * k, scale | k);
        if (!scale && k == kG2Head - 1) nb_sync_if(wg == 0, NB_ST0, 256);
      }
      wg_commit();
    };
    constexpr uint32_t dae = ((sd + OFF_HE) >> 4) | (64u << 16), dal = ((sd + OFF_A) >> 4) | (64u << 16);
    {
      const uint32_t da = wg ? dal : dae, da5 = wg ? ((sd + OFF_HL5) >> 4) | (64u << 16) : dae + 5 * 512;
      mbar_wait(sb + B_WF, 0);
      mbar_wait(sb + B_HE - 48 * wg, 0);
      if (wg == 0) nb_sync(NB_GO0, 256);
#pragma unroll
      for (int st = 0; st < 6; st++) {
        g2_stage(st < 5 ? da + 512 * st : da5, st, 4, st);
        if (st < 5) mbar_wait(sb + B_HE - 48 * wg + 8 * (st + 1), 0);
        if (st == 4) mbar_wait(sb + B_W5, 0);
        if (st > 0) {
          wg_wait<1>();
          if (lane == 0) { if (!wg) mbar_arrive(sb + B_EMPTYH + 8 * (st - 1)); mbar_arrive(sb + B_EMPTYW + 8 * (st - 1)); }
        }
      }
    }
    auto send_ok = [&]() { if (lane == 0) asm volatile("mbarrier.arrive.shared::cluster.b64 _, [%0];" ::"r"(peer + B_SENDOK) : "memory"); };
    if (!keeper) {
#pragma unroll
      for (int s = 0; s < 5; s++) {
        mbar_wait(sb + B_FULL3 + 8 * s, 0);
        g2_stage(dae + 512 * s, s, s < 4 ? 4 : 3, 1);
        if (s == 0) { wg_wait<1>(); send_ok(); }
      }
      nb_arrive(NB_SENT, 256);
      if (lane == 0) mbar_arrive(sb + B_DONE);
      mbar_wait(sb + B_SENDOK, 0);
      wg_wait<0>();
      pin(d);
      const uint32_t dst = peer + OFF_RECV + w4 * 4096 + lane * 16;
#pragma unroll
      for (int jj = 0; jj < 8; jj++)
        asm volatile("st.async.shared::cluster.mbarrier::complete_tx::bytes.v4.b32 [%0], {%1, %2, %3, %4}, [%5];"
                     ::"r"(dst + jj * 512), "r"(pack_bf16(d[8 * jj], d[8 * jj + 1])), "r"(pack_bf16(d[8 * jj + 2], d[8 * jj + 3])),
                       "r"(pack_bf16(d[8 * jj + 4], d[8 * jj + 5])), "r"(pack_bf16(d[8 * jj + 6], d[8 * jj + 7])), "r"(peer + B_RECV) : "memory");
    } else {
      wg_wait<0>();
      send_ok();
      mbar_wait(sb + B_KH, 0);
      const uint32_t ya = sb + OFF_P + (8 * (mat >> 1) + ii) * 128 + 16 * ((2 * w4 + (mat & 1)) ^ ii);
      const uint32_t ra = sb + OFF_RECV + w4 * 4096 + lane * 16;
      const uint32_t oa = sb + OFF_RECV + w4 * 4096 + (ii + 8 * (mat & 1)) * 128;
      const uint32_t ga = lds32(sb + OFF_GATE + 4 * (16 * w4 + (lane >> 2))), gb = lds32(sb + OFF_GATE + 4 * (16 * w4 + (lane >> 2)) + 32);
      const uint32_t g0 = __byte_perm(ga, 0, 0x1010), g1 = __byte_perm(gb, 0, 0x1010);
      const uint32_t o0 = __byte_perm(ga, 0, 0x3232), o1 = __byte_perm(gb, 0, 0x3232);
      nb_sync(NB_SENT, 256);
#pragma unroll
      for (int s = 0; s < 5; s++) g2_stage(dal + 512 * s, s, s < 4 ? 4 : 3, 1);
      if (lane == 0) mbar_arrive(sb + B_DONE);
      uint32_t yv[32];
      float4 rv[8];
      mbar_wait(sb + B_YFULL, 0);
#pragma unroll
      for (int jj = 0; jj < 4; jj++) ldsm4t(ya + jj * 2048, yv + 4 * jj);
      mbar_wait(sb + B_RECV, 0);
#pragma unroll
      for (int jj = 0; jj < 8; jj++) {
        rv[jj] = ldsf4(ra + jj * 512);
        if (jj >= 4) ldsm4t(ya + jj * 2048, yv + 4 * jj);
      }
      wg_wait<0>();
      pin(d);
#pragma unroll
      for (int jj = 0; jj < 8; jj++) {
        const uint32_t r[4] = {__float_as_uint(rv[jj].x), __float_as_uint(rv[jj].y), __float_as_uint(rv[jj].z), __float_as_uint(rv[jj].w)};
#pragma unroll
        for (int e = 0; e < 4; e++) {
          const uint32_t o = (e & 1) ? o1 : o0;
          yv[4 * jj + e] = bfma2((e & 1) ? g1 : g0, yv[4 * jj + e], bmul2(o, badd2(r[e], pack_bf16(d[8 * jj + 2 * e], d[8 * jj + 2 * e + 1]))));
        }
        stsm4(oa + (jj >> 2) * 2048 + 16 * ((2 * (jj & 3) + (mat >> 1)) ^ ii), yv[4 * jj], yv[4 * jj + 1], yv[4 * jj + 2], yv[4 * jj + 3]);
        if ((jj & 3) == 3) {
          fence_async_smem();
          __syncwarp();
          if (elect()) tma3d_store(tm.m + TM_OUT, sb + OFF_RECV + w4 * 4096 + (jj >> 2) * 2048, 0, 64 * tb + 16 * w4, 2 * cq + (jj >> 2));
        }
      }
      if (elect()) {
        asm volatile("cp.async.bulk.commit_group;" ::: "memory");
        asm volatile("cp.async.bulk.wait_group.read 0;" ::: "memory");
      }
      __syncwarp();
    }
  }
}

__device__ float g_fb_taps[kD * kL];
__global__ void fb_taps(const Params p) {
  const int ch = blockIdx.x;
  const float dt = bf_round(expf(__bfloat162float(p.log_dt[ch])));
  for (int l = threadIdx.x; l < kL; l += blockDim.x) {
    const float pos = bf_round((float)l);
    float s = 0.f;
    for (int n = ch * 128; n < ch * 128 + 128; n++) {
      float sn, cs;
      sincosf(__bfloat162float(p.a_im[n]) * dt * pos, &sn, &cs);
      s += expf(-bf_round(expf(__bfloat162float(p.log_a[n]))) * dt * pos) * (__bfloat162float(p.c_re[n]) * cs - __bfloat162float(p.c_im[n]) * sn);
    }
    g_fb_taps[l * kD + ch] = 2.f * dt * s;
  }
}
__global__ void fb_token(const Params p, __nv_bfloat16* out) {
  __shared__ float xs[kD], hs[kF], logit;
  const int t = blockIdx.x, c = threadIdx.x;
  xs[c] = __bfloat162float(p.x[t * kD + c]);
  __syncthreads();
  if (c == 0) {
    float s = 0.f;
    for (int k = 0; k < kD; k++) s += bf_round(xs[k] * __bfloat162float(p.gate_w[k]));
    logit = bf_round(s);
  }
  for (int f = c; f < kF; f += kD) {
    float g = 0.f, u = 0.f;
    for (int k = 0; k < kD; k++) { g += xs[k] * __bfloat162float(p.w_gate[k * kF + f]); u += xs[k] * __bfloat162float(p.w_up[k * kF + f]); }
    hs[f] = bf_round(g / (1.f + expf(-g)) * u);
  }
  __syncthreads();
  float b = 0.f, a = xs[c] * __bfloat162float(p.d_skip[c]);
  for (int f = 0; f < kF; f++) b += hs[f] * __bfloat162float(p.w_down[f * kD + c]);
  for (int l = 0; l <= t; l++) a += g_fb_taps[l * kD + c] * __bfloat162float(p.x[(t - l) * kD + c]);
  const float g = bf_round(1.f / (1.f + expf(-logit)));
  out[t * kD + c] = __float2bfloat16_rn(g * a + bf_round(1.f - g) * b);
}

typedef CUresult (*EncodeFn)(CUtensorMap*, CUtensorMapDataType, cuuint32_t, void*, const cuuint64_t*, const cuuint64_t*,
                             const cuuint32_t*, const cuuint32_t*, CUtensorMapInterleave, CUtensorMapSwizzle,
                             CUtensorMapL2promotion, CUtensorMapFloatOOBfill);

static void encode(EncodeFn fn, CUtensorMap* m, const void* base, int rank, const cuuint64_t* dims, const cuuint64_t* strides,
                   const cuuint32_t* box, CUtensorMapSwizzle sw) {
  const cuuint32_t es[4] = {1, 1, 1, 1};
  fn(m, CU_TENSOR_MAP_DATA_TYPE_BFLOAT16, rank, const_cast<void*>(base), dims, strides, box, es, CU_TENSOR_MAP_INTERLEAVE_NONE, sw,
     CU_TENSOR_MAP_L2_PROMOTION_L2_128B, CU_TENSOR_MAP_FLOAT_OOB_FILL_NONE);
}

extern "C" void kernel_launch(void* const* d_in, const int* in_sizes, int n_in, void* d_out, int out_size) {
  void* fp = nullptr;
  cudaDriverEntryPointQueryResult qr;
  cudaGetDriverEntryPoint("cuTensorMapEncodeTiled", &fp, cudaEnableDefault, &qr);
  EncodeFn fn = (EncodeFn)fp;
  Maps tm;
  {
    const cuuint64_t dims[2] = {kD, kL}, st[1] = {kD * 2};
    const cuuint32_t box[2] = {32, 128};
    encode(fn, tm.m + TM_X, d_in[0], 2, dims, st, box, CU_TENSOR_MAP_SWIZZLE_64B);
  }
  {
    const cuuint64_t dims[3] = {512, kD, 2}, dim3[2] = {kF, kD}, st[2] = {kF * 2, 1024};
    const cuuint32_t box[3] = {64, 32, 2}, box3[2] = {40, 32};
    encode(fn, tm.m + TM_WG, d_in[8], 3, dims, st, box, CU_TENSOR_MAP_SWIZZLE_128B);
    encode(fn, tm.m + TM_WU, d_in[9], 3, dims, st, box, CU_TENSOR_MAP_SWIZZLE_128B);
    encode(fn, tm.m + TM_WG3, d_in[8], 2, dim3, st, box3, CU_TENSOR_MAP_SWIZZLE_128B);
    encode(fn, tm.m + TM_WU3, d_in[9], 2, dim3, st, box3, CU_TENSOR_MAP_SWIZZLE_128B);
    const cuuint32_t boxx[2] = {32, 64};
    encode(fn, tm.m + TM_WGX, d_in[8], 2, dim3, st, boxx, CU_TENSOR_MAP_SWIZZLE_64B);
    encode(fn, tm.m + TM_WUX, d_in[9], 2, dim3, st, boxx, CU_TENSOR_MAP_SWIZZLE_64B);
  }
  {
    const cuuint64_t st[2] = {kD * 2, 128};
    const cuuint32_t box[3] = {64, 64, 2};
    const cuuint64_t dw[3] = {64, kF, 8}, dx[3] = {64, kL, 8};
    encode(fn, tm.m + TM_WD, d_in[10], 3, dw, st, box, CU_TENSOR_MAP_SWIZZLE_128B);
    const cuuint32_t boxo[3] = {64, 16, 1};
    encode(fn, tm.m + TM_OUT, d_out, 3, dx, st, boxo, CU_TENSOR_MAP_SWIZZLE_128B);
  }
  {
    void* u = nullptr;
    cudaGetSymbolAddress(&u, g_u);
    const cuuint64_t dims[3] = {1024, 512, 2}, st[2] = {2048, 512 * 2048};
    const cuuint32_t box[3] = {64, 64, 2};
    encode(fn, tm.m + TM_U, u, 3, dims, st, box, CU_TENSOR_MAP_SWIZZLE_128B);
    const cuuint64_t diml[4] = {64, 16, 2, 512}, stl[3] = {128, 512 * 2048, 2048};
    const cuuint32_t boxl[4] = {64, 17, 2, 4};
    encode(fn, tm.m + TM_UL, u, 4, diml, stl, boxl, CU_TENSOR_MAP_SWIZZLE_NONE);
  }
  {
    const cuuint64_t dims[4] = {kD, 8, 8, 32}, st[3] = {8 * kD * 2, kD * 2, 64 * kD * 2};
    const cuuint32_t box[4] = {64, 8, 8, 2};
    encode(fn, tm.m + TM_XP, d_in[0], 4, dims, st, box, CU_TENSOR_MAP_SWIZZLE_128B);
  }
  Params p;
  p.x = (const __nv_bfloat16*)d_in[0];      p.log_a = (const __nv_bfloat16*)d_in[1];
  p.a_im = (const __nv_bfloat16*)d_in[2];   p.c_re = (const __nv_bfloat16*)d_in[3];
  p.c_im = (const __nv_bfloat16*)d_in[4];   p.log_dt = (const __nv_bfloat16*)d_in[5];
  p.d_skip = (const __nv_bfloat16*)d_in[6]; p.w_down = (const __nv_bfloat16*)d_in[10];
  p.gate_w = (const __nv_bfloat16*)d_in[11];
  p.w_gate = (const __nv_bfloat16*)d_in[8]; p.w_up = (const __nv_bfloat16*)d_in[9];
  p.first[0] = p.x; p.first[1] = p.w_gate; p.first[2] = p.w_up;
  cudaFuncSetAttribute(gated_mix_kernel, cudaFuncAttributeMaxDynamicSharedMemorySize, SMEM_BYTES);
  cudaLaunchConfig_t cfg = {};
  cudaLaunchAttribute attr;
  attr.id = cudaLaunchAttributeClusterDimension;
  attr.val.clusterDim.x = 2; attr.val.clusterDim.y = 1; attr.val.clusterDim.z = 1;
  cfg.gridDim = 132; cfg.blockDim = 512; cfg.dynamicSmemBytes = SMEM_BYTES; cfg.attrs = &attr; cfg.numAttrs = 1;
  int clusters = 0;
  cudaOccupancyMaxActiveClusters(&clusters, gated_mix_kernel, &cfg);
  if (clusters >= kClusters) {
    gated_mix_kernel<<<132, 512, SMEM_BYTES>>>(p, tm);
  } else {
    fb_taps<<<kD, 256>>>(p);
    fb_token<<<kL, kD>>>(p, (__nv_bfloat16*)d_out);
  }
}
```
